```python
import torch

def _softmax(x, axis=-1):
    return torch.softmax(x, dim=axis)
def _gelu(x):
    return torch.nn.functional.gelu(x, approximate="tanh")
def _silu(x):
    return torch.nn.functional.silu(x)
def _sigmoid(x):
    return torch.sigmoid(x)
def _layernorm(x, axis=-1, eps=1e-5):
    m = x.mean(dim=axis, keepdim=True)
    v = x.var(dim=axis, keepdim=True, unbiased=False)
    return (x - m) / torch.sqrt(v + eps)
def _scatter_add(tgt, idx, src, axis=0):
    return tgt.clone().index_add_(axis, idx, src)
def _segment_sum(src, seg, n):
    out = torch.zeros((n,) + src.shape[1:], dtype=src.dtype)
    return out.index_add_(0, seg, src)
def _pad(x, pw):
    flat = tuple(v for pair in reversed(pw) for v in pair)
    return torch.nn.functional.pad(x, flat)

kernel_name = 'standalone__edge_featured_mpnn_mpnn__graph'

def setup_inputs():

    _w = (lambda a: (lambda t: t.to(torch.bfloat16) if t.is_floating_point() else t)(torch.as_tensor(a)))
    N, deg, D, De = 25000, 32, 64, max(16, 1)
    E = N * deg
    H = 2 * D
    return {
        "x": _w((lambda *s: torch.randn(*s, dtype=torch.bfloat16) * 0.05)(N, D)),
        "e_attr": _w((lambda *s: torch.randn(*s, dtype=torch.bfloat16) * 0.8)(E, De)),
        "src": _w((lambda lo, hi, *s: torch.randint(lo, hi, s))(0, N, E).to(torch.int64)),
        "dst": _w((lambda lo, hi, *s: torch.randint(lo, hi, s))(0, N, E).to(torch.int64)),
        "w1": _w((lambda *s: torch.randn(*s, dtype=torch.bfloat16) * 0.8)(2 * D + De, H) * (1.0 / (2 * D + De) ** 0.5)),
        "b1": _w((lambda *s: torch.randn(*s, dtype=torch.bfloat16) * 0.8)(H) * 0.01),
        "w2": _w((lambda *s: torch.randn(*s, dtype=torch.bfloat16) * 0.05)(H, D) * (1.0 / H ** 0.5)),
        "b2": _w((lambda *s: torch.randn(*s, dtype=torch.bfloat16) * 0.05)(D) * 0.01),
    }

def reference(x, e_attr, src, dst, w1, b1, w2, b2):
    N, D = x.shape
    h_src = x[src]
    h_dst = x[dst]
    m_in = torch.concatenate([h_src, h_dst, e_attr], axis=-1)
    h = _silu(m_in @ w1 + b1)
    msg = h @ w2 + b2
    return _segment_sum(msg, dst, N)
```

```cpp
#include <cuda_runtime.h>
#include <cuda_bf16.h>
#include <stdint.h>

namespace {

constexpr int NN   = 25000;
constexpr int NE   = 800000;
constexpr int G    = 132;
constexpr int NPB  = 190;
constexpr int CH   = 6064;
constexpr int RUNS = 96;
constexpr int RUNP = 98;
constexpr int CAPT = 54;
constexpr int CAP  = CAPT * 128;
constexpr int OVF  = 128;
constexpr int NT   = 384;

constexpr int SM_XE   = 0;
constexpr int XE_ST   = 20480;
constexpr int SM_IND  = 81920;
constexpr int SM_QA   = 106496;
constexpr int SM_LA   = 155648;
constexpr int SM_LB   = SM_LA + CAP * 4;
constexpr int SM_W2   = SM_LA + CAP * 8;
constexpr int SM_MISC = SM_W2 + 16384;
constexpr int SM_CNT   = SM_MISC;
constexpr int SM_DEG   = SM_CNT + 640;
constexpr int SM_BASE  = SM_DEG + 768;
constexpr int SM_FIRST = SM_BASE + 768;
constexpr int SM_BAR   = SM_FIRST + 256;
constexpr int SM_FLAG  = SM_BAR + 64;
constexpr int SM_TOTAL = SM_FLAG + 16;
constexpr int SM_STG  = 0;
constexpr int SM_OVF  = G * RUNP * 8;
constexpr int SM_W1   = SM_LA;
static_assert(SM_OVF + OVF * 16 <= SM_QA, "overflow buffer");
static_assert(SM_TOTAL <= 232448, "smem");
static_assert(SM_W2 % 1024 == 0 && SM_LA % 1024 == 0 && SM_QA % 1024 == 0, "align");

__device__ uint4 g_rec[G * G * RUNS / 2];
__device__ unsigned g_epoch;
#define TSTAMP(i, cond)
#define CSTAMP(i, cond)

__device__ __forceinline__ uint64_t mkdesc(uint32_t addr, uint32_t lbo, uint32_t sbo, uint32_t swz) {
    return (uint64_t)((addr & 0x3FFFF) >> 4) | ((uint64_t)(lbo >> 4) << 16) | ((uint64_t)(sbo >> 4) << 32) |
           ((uint64_t)swz << 62);
}
__device__ __forceinline__ void wg_fence()  { asm volatile("wgmma.fence.sync.aligned;" ::: "memory"); }
__device__ __forceinline__ void wg_commit() { asm volatile("wgmma.commit_group.sync.aligned;" ::: "memory"); }
template <int N> __device__ __forceinline__ void wg_wait() { asm volatile("wgmma.wait_group.sync.aligned %0;" ::"n"(N) : "memory"); }
__device__ __forceinline__ void fence_async() { asm volatile("fence.proxy.async.shared::cta;" ::: "memory"); }

#define R8(d, o) "+f"(d[o + 0]), "+f"(d[o + 1]), "+f"(d[o + 2]), "+f"(d[o + 3]), "+f"(d[o + 4]), "+f"(d[o + 5]), "+f"(d[o + 6]), "+f"(d[o + 7])
#define W8(d, o) "=f"(d[o + 0]), "=f"(d[o + 1]), "=f"(d[o + 2]), "=f"(d[o + 3]), "=f"(d[o + 4]), "=f"(d[o + 5]), "=f"(d[o + 6]), "=f"(d[o + 7])
#define L64 "{%0,%1,%2,%3,%4,%5,%6,%7,%8,%9,%10,%11,%12,%13,%14,%15,%16,%17,%18,%19,%20,%21,%22,%23,%24,%25,%26,%27,%28,%29,%30,%31,%32,%33,%34,%35,%36,%37,%38,%39,%40,%41,%42,%43,%44,%45,%46,%47,%48,%49,%50,%51,%52,%53,%54,%55,%56,%57,%58,%59,%60,%61,%62,%63}"
#define L32 "{%0,%1,%2,%3,%4,%5,%6,%7,%8,%9,%10,%11,%12,%13,%14,%15,%16,%17,%18,%19,%20,%21,%22,%23,%24,%25,%26,%27,%28,%29,%30,%31}"

__device__ __forceinline__ void rs128_first(float* d, const uint32_t* a, uint64_t db) {
    asm volatile("{.reg .pred p; setp.ne.b32 p, 0, 0;\n"
                 "wgmma.mma_async.sync.aligned.m64n128k16.f32.bf16.bf16 " L64 ", {%64,%65,%66,%67}, %68, p, 1, 1, 0;}"
                 : W8(d, 0), W8(d, 8), W8(d, 16), W8(d, 24), W8(d, 32), W8(d, 40), W8(d, 48), W8(d, 56)
                 : "r"(a[0]), "r"(a[1]), "r"(a[2]), "r"(a[3]), "l"(db));
}
__device__ __forceinline__ void rs128(float* d, const uint32_t* a, uint64_t db) {
    asm volatile("{.reg .pred p; setp.eq.b32 p, 0, 0;\n"
                 "wgmma.mma_async.sync.aligned.m64n128k16.f32.bf16.bf16 " L64 ", {%64,%65,%66,%67}, %68, p, 1, 1, 0;}"
                 : R8(d, 0), R8(d, 8), R8(d, 16), R8(d, 24), R8(d, 32), R8(d, 40), R8(d, 48), R8(d, 56)
                 : "r"(a[0]), "r"(a[1]), "r"(a[2]), "r"(a[3]), "l"(db));
}
__device__ __forceinline__ void rs16t(float* d, const uint32_t* a, uint64_t db) {
    asm volatile("{.reg .pred p; setp.eq.b32 p, 0, 0;\n"
                 "wgmma.mma_async.sync.aligned.m64n16k16.f32.bf16.bf16 {%0,%1,%2,%3,%4,%5,%6,%7}, {%8,%9,%10,%11}, %12, p, 1, 1, 1;}"
                 : R8(d, 0)
                 : "r"(a[0]), "r"(a[1]), "r"(a[2]), "r"(a[3]), "l"(db));
}
__device__ __forceinline__ void ss128t(float* d, uint64_t da, uint64_t db, int acc) {
    asm volatile("{.reg .pred p; setp.ne.b32 p, %66, 0;\n"
                 "wgmma.mma_async.sync.aligned.m64n128k16.f32.bf16.bf16 " L64 ", %64, %65, p, 1, 1, 0, 1;}"
                 : R8(d, 0), R8(d, 8), R8(d, 16), R8(d, 24), R8(d, 32), R8(d, 40), R8(d, 48), R8(d, 56)
                 : "l"(da), "l"(db), "r"(acc));
}
__device__ __forceinline__ void ss64t(float* d, uint64_t da, uint64_t db, int acc) {
    asm volatile("{.reg .pred p; setp.ne.b32 p, %34, 0;\n"
                 "wgmma.mma_async.sync.aligned.m64n64k16.f32.bf16.bf16 " L32 ", %32, %33, p, 1, 1, 0, 1;}"
                 : R8(d, 0), R8(d, 8), R8(d, 16), R8(d, 24)
                 : "l"(da), "l"(db), "r"(acc));
}
template <int NREG> __device__ __forceinline__ void fence_regs(float* d) {
#pragma unroll
    for (int i = 0; i < NREG; i++) asm volatile("" : "+f"(d[i])::"memory");
}
template <int NREG> __device__ __forceinline__ void fence_regs(uint32_t* d) {
#pragma unroll
    for (int i = 0; i < NREG; i++) asm volatile("" : "+r"(d[i])::"memory");
}
__device__ __forceinline__ void ldsm4t(uint32_t* r, uint32_t addr) {
    asm volatile("ldmatrix.sync.aligned.m8n8.x4.trans.shared.b16 {%0,%1,%2,%3}, [%4];"
                 : "=r"(r[0]), "=r"(r[1]), "=r"(r[2]), "=r"(r[3]) : "r"(addr) : "memory");
}
__device__ __forceinline__ void cp16(uint32_t s, const void* g) {
    asm volatile("cp.async.cg.shared.global [%0], [%1], 16;" ::"r"(s), "l"(g) : "memory");
}
__device__ __forceinline__ void cp16z(uint32_t s, const void* g, int neg) {
    asm volatile("{.reg .pred p; setp.lt.s32 p, %2, 0;\n"
                 "cp.async.cg.shared.global [%0], [%1], 16, p;}" ::"r"(s), "l"(g), "r"(neg) : "memory");
}
__device__ __forceinline__ void cp4(uint32_t s, const void* g) {
    asm volatile("cp.async.ca.shared.global [%0], [%1], 4;" ::"r"(s), "l"(g) : "memory");
}
__device__ __forceinline__ void mbar_init(uint32_t a, int cnt) { asm volatile("mbarrier.init.shared::cta.b64 [%0], %1;" ::"r"(a), "r"(cnt) : "memory"); }
__device__ __forceinline__ void mbar_arrive(uint32_t a) { asm volatile("mbarrier.arrive.shared::cta.b64 _, [%0];" ::"r"(a) : "memory"); }
__device__ __forceinline__ void mbar_cp_arrive(uint32_t a) { asm volatile("cp.async.mbarrier.arrive.noinc.shared::cta.b64 [%0];" ::"r"(a) : "memory"); }
__device__ __forceinline__ void mbar_wait(uint32_t a, uint32_t parity) {
    asm volatile("{.reg .pred p; .reg .u32 n; mov.u32 n, 0;\n"
                 "MW_%=: mbarrier.try_wait.parity.shared::cta.b64 p, [%0], %1;\n"
                 "@p bra MD_%=;\n"
                 "add.u32 n, n, 1; setp.gt.u32 p, n, 0x100000;\n"
                 "@p trap;\n"
                 "bra MW_%=;\n"
                 "MD_%=: }" ::"r"(a), "r"(parity) : "memory");
}
__device__ __forceinline__ float tanh_fast(float x) { float y; asm("tanh.approx.f32 %0, %1;" : "=f"(y) : "f"(x)); return y; }
__device__ __forceinline__ uint32_t pack2(float lo, float hi) {
    uint32_t r; asm("cvt.rn.bf16x2.f32 %0, %1, %2;" : "=r"(r) : "f"(hi), "f"(lo)); return r;
}
__device__ __forceinline__ float bf_lo(uint32_t v) { return __uint_as_float(v << 16); }
__device__ __forceinline__ float bf_hi(uint32_t v) { return __uint_as_float(v & 0xFFFF0000u); }
__device__ __forceinline__ uint32_t lds32(uint32_t a) { uint32_t v; asm volatile("ld.shared.b32 %0, [%1];" : "=r"(v) : "r"(a) : "memory"); return v; }
__device__ __forceinline__ uint4 lds128(uint32_t a) {
    uint4 v; asm volatile("ld.shared.v4.b32 {%0,%1,%2,%3}, [%4];" : "=r"(v.x), "=r"(v.y), "=r"(v.z), "=r"(v.w) : "r"(a) : "memory"); return v;
}
__device__ __forceinline__ void sts32(uint32_t a, uint32_t v) { asm volatile("st.shared.b32 [%0], %1;" ::"r"(a), "r"(v) : "memory"); }
__device__ __forceinline__ void sts64(uint32_t a, uint32_t x, uint32_t y) { asm volatile("st.shared.v2.b32 [%0], {%1,%2};" ::"r"(a), "r"(x), "r"(y) : "memory"); }
__device__ __forceinline__ void sts128(uint32_t a, uint32_t x, uint32_t y, uint32_t z, uint32_t w) {
    asm volatile("st.shared.v4.b32 [%0], {%1,%2,%3,%4};" ::"r"(a), "r"(x), "r"(y), "r"(z), "r"(w) : "memory");
}
__device__ __forceinline__ uint32_t atoms_inc(uint32_t a) {
    uint32_t v; asm volatile("atom.shared.add.u32 %0, [%1], 1;" : "=r"(v) : "r"(a) : "memory"); return v;
}
__device__ __forceinline__ void st_rec(uint4* p, uint4 v) {
    uint64_t a = (uint64_t)v.x | ((uint64_t)v.y << 32), b = (uint64_t)v.z | ((uint64_t)v.w << 32);
    asm volatile("st.relaxed.gpu.global.v2.b64 [%0], {%1,%2};" ::"l"(p), "l"(a), "l"(b) : "memory");
}
__device__ __forceinline__ uint4 ld_rec(const uint4* p) {
    uint64_t a, b;
    asm volatile("ld.relaxed.gpu.global.v2.b64 {%0,%1}, [%2];" : "=l"(a), "=l"(b) : "l"(p) : "memory");
    return make_uint4((uint32_t)a, (uint32_t)(a >> 32), (uint32_t)b, (uint32_t)(b >> 32));
}
__device__ __forceinline__ int4 ld_stream(const int4* p) {
    int4 v;
    asm volatile("ld.global.nc.L1::no_allocate.v4.s32 {%0,%1,%2,%3}, [%4];" : "=r"(v.x), "=r"(v.y), "=r"(v.z), "=r"(v.w) : "l"(p));
    return v;
}
__device__ __forceinline__ int pos2col(int p) { return (p & ~15) | ((p & 1) << 3) | ((p >> 1) & 7); }

__device__ __forceinline__ void tail_gemm(uint32_t sb, int wg, int warp4, int lane, int bucket,
                                          const __nv_bfloat16* __restrict__ b2, __nv_bfloat16* __restrict__ out) {
    const int g = lane >> 2, q = lane & 3;
    const uint4 bb0 = __ldg(reinterpret_cast<const uint4*>(b2) + 2 * q);
    const uint4 bb1 = __ldg(reinterpret_cast<const uint4*>(b2) + 2 * q + 1);
    fence_async();
    asm volatile("bar.sync 1, 384;" ::: "memory");
    float d[32];
#pragma unroll
    for (int i = 0; i < 32; i++) d[i] = 0.f;
    wg_fence();
#pragma unroll
    for (int ks = 0; ks < 8; ks++) {
        uint64_t da = mkdesc(sb + SM_QA + (ks >> 2) * 24576 + wg * 8192 + (ks & 3) * 32, 16, 1024, 1);
        uint64_t db = mkdesc(sb + SM_W2 + ks * 2048, 16, 1024, 1);
        ss64t(d, da, db, ks);
    }
    wg_commit();
    wg_wait<0>();
    fence_regs<32>(d);
    const uint32_t bw[8] = {bb0.x, bb0.y, bb0.z, bb0.w, bb1.x, bb1.y, bb1.z, bb1.w};
#pragma unroll
    for (int r = 0; r < 2; r++) {
        const int node = wg * 64 + warp4 * 16 + g + 8 * r;
        const int gn = bucket * NPB + node;
        if (node < NPB && gn < NN) {
            const uint32_t dg = lds32(sb + SM_DEG + node * 4);
            const float fd = (float)dg;
            uint32_t o[8];
#pragma unroll
            for (int j = 0; j < 8; j++) {
                float v0 = fmaf(fd, bf_lo(bw[j]), d[4 * j + 2 * r]);
                float v1 = fmaf(fd, bf_hi(bw[j]), d[4 * j + 2 * r + 1]);
                o[j] = dg ? pack2(v0, v1) : 0u;
            }
            uint4* op = reinterpret_cast<uint4*>(out + (size_t)gn * 64 + 16 * q);
            op[0] = make_uint4(o[0], o[1], o[2], o[3]);
            op[1] = make_uint4(o[4], o[5], o[6], o[7]);
        }
    }
}

struct Cons {
    uint32_t sb, qa_l;
    int slot_l, chunk_l;
    int lane, q;
    uint32_t fl_addr;
    int fl_chunk;
};

__device__ __forceinline__ void load_q(uint32_t* qf, const Cons& c, int first) {
    int node = first + ((c.slot_l - first) & 15);
    node = min(node, 191);
    ldsm4t(qf, c.qa_l + node * 128 + ((c.chunk_l ^ (node & 7)) << 4));
}
__device__ __forceinline__ void issue_g1(float* acc, const uint32_t (*w1)[4], const uint32_t* qf, uint32_t sb, int st, int ist) {
    const uint64_t dx = mkdesc(sb + SM_XE + st * XE_ST, 16, 1024, 1);
    const uint64_t de = mkdesc(sb + SM_XE + st * XE_ST + 16384, 16, 256, 3);
    const uint64_t di = mkdesc(sb + SM_IND + ist * 4096, 16, 256, 3);
    rs128_first(acc, w1[0], dx);
    rs128(acc, w1[1], dx + 2);
    rs128(acc, w1[2], dx + 4);
    rs128(acc, w1[3], dx + 6);
    rs128(acc, w1[4], de);
    rs128(acc, qf, di);
    wg_commit();
}
__device__ __forceinline__ void flush_nodes(float* agg, const Cons& c, int f0, int f1) {
#pragma unroll
    for (int j = 0; j < 4; j++) {
        const int s = 2 * c.q + (j & 1) + 8 * (j >> 1);
        const int node = f0 + ((s - f0) & 15);
        const int i0 = (j >> 1) * 4 + (j & 1);
        if (node < f1) {
            sts32(c.fl_addr + node * 128 + ((c.fl_chunk ^ (node & 7)) << 4), pack2(agg[i0], agg[i0 + 2]));
            agg[i0] = 0.f;
            agg[i0 + 2] = 0.f;
        }
    }
}
__device__ __forceinline__ float silu2(float a, float b) {
    const float ta = tanh_fast(a), tb = tanh_fast(b);
    return fmaf(b, tb, fmaf(a, ta, a + b));
}

__device__ __forceinline__ void issue_agg(float* agg, const uint32_t* pk, uint32_t sb, int ist) {
    const uint64_t da = mkdesc(sb + SM_IND + ist * 4096, 16, 512, 3);
#pragma unroll
    for (int kk = 0; kk < 4; kk++) rs16t(agg, pk + 4 * kk, da + kk * 64);
    wg_commit();
}
__device__ __forceinline__ void cons_step(float* cur, float* nxt, float* agg, const uint32_t (*w1)[4], uint32_t* pk,
                                          const Cons& c, int t, int T, int& iprev, int& icur, int& fprev, int& fcur) {
    const uint32_t sb = c.sb;
    uint32_t qf[4];
    const int fnext = (int)lds32(sb + SM_FIRST + (t + 1) * 4);
    load_q(qf, c, fnext);
    const int inext = (icur == 5) ? 0 : icur + 1;
    if (t + 1 < T) mbar_wait(sb + SM_BAR + ((t + 1) & 3) * 8, ((t + 1) >> 2) & 1);
    fence_async();
    wg_fence();
    issue_agg(agg, pk, sb, iprev);
    issue_g1(nxt, w1, qf, sb, (t + 1) & 3, inext);
    float s[32];
#pragma unroll
    for (int J = 0; J < 4; J++)
#pragma unroll
        for (int i = 0; i < 4; i++) s[4 * J + i] = silu2(cur[8 * J + i], cur[8 * J + 4 + i]);
    fence_regs<16>(s);
    wg_wait<1>();
    fence_regs<8>(agg);
    fence_regs<16>(pk);
    flush_nodes(agg, c, fprev, fcur);
#pragma unroll
    for (int J = 4; J < 8; J++)
#pragma unroll
        for (int i = 0; i < 4; i++) s[4 * J + i] = silu2(cur[8 * J + i], cur[8 * J + 4 + i]);
#pragma unroll
    for (int i = 0; i < 16; i++) pk[i] = pack2(s[2 * i], s[2 * i + 1]);
    fence_regs<16>(pk);
    wg_wait<0>();
    fence_regs<64>(nxt);
    if (c.lane == 0) mbar_arrive(sb + SM_BAR + 32 + ((t + 1) & 3) * 8);
    iprev = icur;
    icur = inext;
    fprev = fcur;
    fcur = fnext;
}

__device__ __forceinline__ void slow_path(uint32_t sb, int bucket, const __nv_bfloat16* __restrict__ x,
                                       const __nv_bfloat16* __restrict__ ea, const int* __restrict__ src,
                                       const int* __restrict__ dst, const __nv_bfloat16* __restrict__ w1) {
    const int tid = threadIdx.x, lane = tid & 31, j = tid & 127, wg = tid >> 7;
    for (int i = tid; i < NPB * 128; i += NT) sts32(sb + i * 4, 0u);
    if (tid < 192) sts32(sb + SM_DEG + tid * 4, 0u);
    float w[80];
#pragma unroll
    for (int k = 0; k < 80; k++) w[k] = 0.5f * __bfloat162float(w1[(k < 64 ? k : k + 64) * 128 + j]);
    __syncthreads();
    const uint32_t qaddr = sb + SM_QA + (j >> 6) * 24576 + (j & 7) * 2;
    for (int e0 = wg * 32; e0 < NE; e0 += 96) {
        const int dn = dst[e0 + lane] - bucket * NPB;
        unsigned m = __ballot_sync(0xFFFFFFFFu, dn >= 0 && dn < NPB);
        while (m) {
            const int l = __ffs(m) - 1;
            m &= m - 1;
            const int node = __shfl_sync(0xFFFFFFFFu, dn, l);
            const int e = e0 + l;
            const uint4* xr = reinterpret_cast<const uint4*>(x + (size_t)src[e] * 64);
            const uint4* er = reinterpret_cast<const uint4*>(ea + (size_t)e * 16);
            uint16_t qv;
            asm volatile("ld.shared.u16 %0, [%1];" : "=h"(qv) : "r"(qaddr + node * 128 + ((((j & 63) >> 3) ^ (node & 7)) << 4)) : "memory");
            float h = __uint_as_float((uint32_t)qv << 16);
#pragma unroll
            for (int k = 0; k < 10; k++) {
                const uint4 v = (k < 8) ? __ldg(xr + k) : __ldg(er + (k - 8));
                h = fmaf(bf_lo(v.x), w[8 * k + 0], h); h = fmaf(bf_hi(v.x), w[8 * k + 1], h);
                h = fmaf(bf_lo(v.y), w[8 * k + 2], h); h = fmaf(bf_hi(v.y), w[8 * k + 3], h);
                h = fmaf(bf_lo(v.z), w[8 * k + 4], h); h = fmaf(bf_hi(v.z), w[8 * k + 5], h);
                h = fmaf(bf_lo(v.w), w[8 * k + 6], h); h = fmaf(bf_hi(v.w), w[8 * k + 7], h);
            }
            const float f = fmaf(h, tanh_fast(h), h);
            asm volatile("red.shared.add.f32 [%0], %1;" ::"r"(sb + (node * 128 + j) * 4), "f"(f) : "memory");
            if (j == 0) atoms_inc(sb + SM_DEG + node * 4);
        }
    }
    __syncthreads();
    for (int i = tid; i < NPB * 64; i += NT) {
        const int node = i >> 6, pr = i & 63;
        const int hid = (pr >> 3) * 16 + (pr & 7);
        const float a = __uint_as_float(lds32(sb + (node * 128 + hid) * 4));
        const float b = __uint_as_float(lds32(sb + (node * 128 + hid + 8) * 4));
        const int ch = (pr & 31) >> 2;
        sts32(sb + SM_QA + (pr >> 5) * 24576 + node * 128 + ((ch ^ (node & 7)) << 4) + (pr & 3) * 4, pack2(a, b));
    }
}

__global__ void __launch_bounds__(NT, 1)
mpnn_kernel(const __nv_bfloat16* __restrict__ x, const __nv_bfloat16* __restrict__ ea, const int* __restrict__ src,
            const int* __restrict__ dst, const __nv_bfloat16* __restrict__ w1, const __nv_bfloat16* __restrict__ b1,
            const __nv_bfloat16* __restrict__ w2, const __nv_bfloat16* __restrict__ b2, __nv_bfloat16* __restrict__ out,
            int mode) {
    extern __shared__ __align__(1024) uint8_t smem[];
    const uint32_t sb = (uint32_t)__cvta_generic_to_shared(smem);
    const int tid = threadIdx.x, lane = tid & 31, warp = tid >> 5, wg = tid >> 7, warp4 = warp & 3;
    const int cta = blockIdx.x;
    TSTAMP(0, tid == 0);
    CSTAMP(1, tid == 0);

    const int e0 = cta * CH;
    const int nv = min(CH, NE - e0) >> 2;
    int4 dv[4], sv[4];
    if (mode & 1) {
#pragma unroll
        for (int j = 0; j < 4; j++)
            if (tid + NT * j < nv) dv[j] = ld_stream(reinterpret_cast<const int4*>(dst + e0) + tid + NT * j);
#pragma unroll
        for (int j = 0; j < 4; j++)
            if (tid + NT * j < nv) sv[j] = ld_stream(reinterpret_cast<const int4*>(src + e0) + tid + NT * j);
    }
    unsigned epoch;
    asm volatile("ld.relaxed.gpu.global.u32 %0, [%1];" : "=r"(epoch) : "l"(&g_epoch) : "memory");
    if (tid < 160) sts32(sb + SM_CNT + tid * 4, 0u);
    if (tid < 192) sts32(sb + SM_DEG + tid * 4, 0u);
    if (tid < 4) {
        sts32(sb + SM_FLAG + tid * 4, 0u);
        mbar_init(sb + SM_BAR + tid * 8, 128 + 4);
        mbar_init(sb + SM_BAR + 32 + tid * 8, 8);
    }
    if (mode & 2) {
        for (int i = tid; i < 144 * 16; i += NT) {
            const int r = i >> 4, c = i & 15;
            cp16(sb + SM_W1 + (c >> 3) * 18432 + r * 128 + (((c & 7) ^ (r & 7)) << 4), w1 + r * 128 + c * 8);
        }
        for (int i = tid; i < 192 * 8; i += NT) {
            const int r = i >> 3, c = i & 7, gn = cta * NPB + r;
            cp16z(sb + SM_QA + r * 128 + ((c ^ (r & 7)) << 4), x + (size_t)min(gn, NN - 1) * 64 + c * 8, NN - 1 - gn);
        }
        for (int i = tid; i < 128 * 32; i += NT) {
            const int kp = i >> 5, u = i & 31;
            const int k = (kp & ~15) | ((kp & 1) << 3) | ((kp >> 1) & 7);
            const int jj = u & 7, qq = u >> 3;
            cp4(sb + SM_W2 + kp * 128 + ((jj ^ (kp & 7)) << 4) + qq * 4, w2 + k * 64 + u * 2);
        }
        asm volatile("cp.async.commit_group;" ::: "memory");
    }
    __syncthreads();
    const uint32_t tag = epoch % 0x7FFFFu + 1u;
    if (mode & 1) {
        if (tid < 16) {
            const int n = nv * 8;
            asm volatile("cp.async.bulk.prefetch.L2.global [%0], %1;" ::"l"(reinterpret_cast<const char*>(ea) + (size_t)e0 * 32 + (size_t)tid * n), "r"(n) : "memory");
        }
        CSTAMP(2, tid == 0);
        uint32_t pos[16];
#pragma unroll
        for (int j = 0; j < 4; j++) {
            if (tid + NT * j < nv) {
                int dd[4] = {dv[j].x, dv[j].y, dv[j].z, dv[j].w};
                int ss[4] = {sv[j].x, sv[j].y, sv[j].z, sv[j].w};
#pragma unroll
                for (int k = 0; k < 4; k++) {
                    const uint32_t b = ((uint32_t)dd[k] * 22076u) >> 22;
                    const uint32_t r = atoms_inc(sb + SM_CNT + b * 4);
                    pos[4 * j + k] = (r < RUNS - 1) ? (b * RUNP + 1 + r) * 8 : 0xFFFFFFFFu;
                    ss[k] |= (dd[k] - b * NPB) << 15;
                }
                sv[j] = make_int4(ss[0], ss[1], ss[2], ss[3]);
            }
        }
#pragma unroll
        for (int j = 0; j < 4; j++) {
            if (tid + NT * j < nv) {
                const int ss[4] = {sv[j].x, sv[j].y, sv[j].z, sv[j].w};
#pragma unroll
                for (int k = 0; k < 4; k++)
                    if (pos[4 * j + k] != 0xFFFFFFFFu)
                        sts64(sb + SM_STG + pos[4 * j + k], ss[k], (tag << 13) | ((tid + NT * j) * 4 + k));
            }
        }
    }
    CSTAMP(3, tid == 0);
    asm volatile("cp.async.wait_all;" ::: "memory");
    fence_async();
    __syncthreads();
    if (mode & 1) {
#pragma unroll
        for (int i = 0; i < 11; i++) {
            const int b = warp * 11 + i;
            const uint32_t n = lds32(sb + SM_CNT + b * 4);
            const int lim = (min(n, (uint32_t)(RUNS - 1)) + 4) & ~3;
            uint4* gp = g_rec + (size_t)(b * G + cta) * (RUNS / 2);
            if (2 * lane < lim) {
                uint4 v = lds128(sb + SM_STG + b * (RUNP * 8) + lane * 16);
                if (lane == 0) { v.x = n; v.y = tag << 13; }
                st_rec(gp + lane, v);
            }
            if (64 + 2 * lane < lim) st_rec(gp + 32 + lane, lds128(sb + SM_STG + b * (RUNP * 8) + 512 + lane * 16));
        }
    }
    if (!(mode & 2)) return;
    CSTAMP(4, tid == 0);

    uint32_t w1r[5][4];
    {
        float d[64];
#pragma unroll
        for (int i = 0; i < 64; i++) d[i] = 0.f;
        wg_fence();
#pragma unroll
        for (int ks = 0; ks < 4; ks++)
            ss128t(d, mkdesc(sb + SM_QA + wg * 8192 + ks * 32, 16, 1024, 1),
                   mkdesc(sb + SM_W1 + (64 + 16 * ks) * 128, 18432, 1024, 1), ks);
        wg_commit();
        const int kr = (lane & 7) + 8 * (lane >> 4), ch = 2 * warp4 + ((lane >> 3) & 1);
#pragma unroll
        for (int ks = 0; ks < 5; ks++) {
            const int r = (ks < 4 ? 16 * ks : 128) + kr;
            ldsm4t(w1r[ks], sb + SM_W1 + (wg & 1) * 18432 + r * 128 + ((ch ^ (r & 7)) << 4));
        }
        uint32_t bv[16];
#pragma unroll
        for (int j = 0; j < 16; j++) bv[j] = __ldg(reinterpret_cast<const uint32_t*>(b1) + 4 * j + (lane & 3));
        wg_wait<0>();
        fence_regs<64>(d);
        if (wg == 0) asm volatile("bar.sync 2, 128;" ::: "memory");
        else if (wg == 1) asm volatile("bar.sync 3, 128;" ::: "memory");
        else asm volatile("bar.sync 4, 128;" ::: "memory");
        const int r0 = wg * 64 + warp4 * 16 + (lane >> 2);
#pragma unroll
        for (int j = 0; j < 16; j++) {
            const float ba = bf_lo(bv[j]), bb = bf_hi(bv[j]);
            const uint32_t a = sb + SM_QA + (j >> 3) * 24576 + r0 * 128 + (((j & 7) ^ (r0 & 7)) << 4) + (lane & 3) * 4;
            sts32(a, pack2(0.5f * (d[4 * j] + ba), 0.5f * (d[4 * j + 1] + bb)));
            sts32(a + 1024, pack2(0.5f * (d[4 * j + 2] + ba), 0.5f * (d[4 * j + 3] + bb)));
        }
    }
    CSTAMP(5, tid == 0);

    uint4 rv[11];
    uint32_t rc[11];
    {
        const uint4* gp = g_rec + (size_t)(cta * G + warp * 11) * (RUNS / 2) + lane;
#pragma unroll
        for (int i = 0; i < 11; i++) rv[i] = ld_rec(gp + i * (RUNS / 2));
        bool bad = false;
#pragma unroll
        for (int i = 0; i < 11; i++) {
            int it = 0;
            while (true) {
                rc[i] = __shfl_sync(0xFFFFFFFFu, rv[i].x, 0);
                const bool ok = (2 * lane > rc[i] || (rv[i].y >> 13) == tag) && (2 * lane + 1 > rc[i] || (rv[i].w >> 13) == tag);
                if (__all_sync(0xFFFFFFFFu, ok) || mode != 3) break;
                if (++it > (1 << 22)) __trap();
                rv[i] = ld_rec(gp + i * (RUNS / 2));
            }
            if (2 * lane <= rc[i] && lane > 0)
                rv[i].y = (rv[i].y & 0x1FFFu) | (atoms_inc(sb + SM_DEG + (rv[i].x >> 15) * 4) << 13);
            if (2 * lane + 1 <= rc[i])
                rv[i].w = (rv[i].w & 0x1FFFu) | (atoms_inc(sb + SM_DEG + (rv[i].z >> 15) * 4) << 13);
            if (rc[i] > 63) {
                if (rc[i] > RUNS - 1) bad = true;
                else {
                    uint4 v;
                    it = 0;
                    while (true) {
                        v = ld_rec(gp + i * (RUNS / 2) + 32 - (lane & 16));
                        const bool ok = lane >= 16 || ((64 + 2 * lane > rc[i] || (v.y >> 13) == tag) && (65 + 2 * lane > rc[i] || (v.w >> 13) == tag));
                        if (__all_sync(0xFFFFFFFFu, ok) || mode != 3) break;
                        if (++it > (1 << 22)) __trap();
                    }
                    const uint32_t eb = (warp * 11 + i) * CH;
#pragma unroll
                    for (int k = 0; k < 2; k++) {
                        if (lane < 16 && 64 + 2 * lane + k <= rc[i]) {
                            const uint32_t a = k ? v.z : v.x, b = k ? v.w : v.y;
                            const uint32_t r = atoms_inc(sb + SM_DEG + (a >> 15) * 4);
                            const uint32_t o = atoms_inc(sb + SM_FLAG);
                            if (o < OVF) sts128(sb + SM_OVF + o * 16, a, eb + (b & 0x1FFFu), r, 0u);
                            else bad = true;
                        }
                    }
                }
            }
        }
        if (bad) sts32(sb + SM_FLAG + 4, 1u);
    }
    CSTAMP(6, tid == 0);
    __syncthreads();
    if (mode == 3 && cta == 0 && tid == 0) g_epoch = epoch + 1;
    if (warp == 0) {
        uint32_t v[6], s = 0;
#pragma unroll
        for (int k = 0; k < 6; k++) { v[k] = s; s += (lds32(sb + SM_DEG + (lane * 6 + k) * 4) + 1) & ~1u; }
        uint32_t inc = s;
#pragma unroll
        for (int o = 1; o < 32; o <<= 1) {
            const uint32_t u = __shfl_up_sync(0xFFFFFFFFu, inc, o);
            if (lane >= o) inc += u;
        }
#pragma unroll
        for (int k = 0; k < 6; k++) sts32(sb + SM_BASE + (lane * 6 + k) * 4, inc - s + v[k]);
        if (lane == 31) sts32(sb + SM_FLAG + 8, inc);
    }
    __syncthreads();
    CSTAMP(7, tid == 0);
    const int total = (int)lds32(sb + SM_FLAG + 8);
    int T = (total + 127) >> 7;
    bool slow = lds32(sb + SM_FLAG + 4) != 0 || total > CAP;
    if (!slow) {
#pragma unroll
        for (int i = 0; i < 11; i++) {
            const uint32_t eb = (warp * 11 + i) * CH;
#pragma unroll
            for (int k = 0; k < 2; k++) {
                const uint32_t a = k ? rv[i].z : rv[i].x, b = k ? rv[i].w : rv[i].y;
                if (2 * lane + k <= rc[i] && 2 * lane + k > 0) {
                    const uint32_t node = a >> 15;
                    const int idx = pos2col((int)(lds32(sb + SM_BASE + node * 4) + (b >> 13)));
                    sts32(sb + SM_LA + idx * 4, ((a & 0x7FFFu) << 7) | ((node & 15) << 24));
                    sts32(sb + SM_LB + idx * 4, (eb + (b & 0x1FFFu)) << 5);
                }
            }
        }
        if (tid < (int)lds32(sb + SM_FLAG)) {
            const uint4 v = lds128(sb + SM_OVF + tid * 16);
            const uint32_t node = v.x >> 15;
            const int idx = pos2col((int)(lds32(sb + SM_BASE + node * 4) + v.z));
            sts32(sb + SM_LA + idx * 4, ((v.x & 0x7FFFu) << 7) | ((node & 15) << 24));
            sts32(sb + SM_LB + idx * 4, v.y << 5);
        }
        if (tid < 192) {
            const int dg = (int)lds32(sb + SM_DEG + tid * 4), b0 = (int)lds32(sb + SM_BASE + tid * 4);
            if (dg & 1) {
                const int idx = pos2col(b0 + dg);
                sts32(sb + SM_LA + idx * 4, 0x80000000u);
                sts32(sb + SM_LB + idx * 4, 0x80000000u);
            }
            for (int t = (b0 + 127) >> 7; t * 128 < b0 + dg; t++) sts32(sb + SM_FIRST + t * 4, tid);
            if (dg > 0 && tid >= 15 && (int)lds32(sb + SM_BASE + (tid - 15) * 4) > (b0 & ~127)) slow = true;
        } else if (tid < 320) {
            const int p = total + tid - 192;
            if (p < T * 128) {
                const int idx = pos2col(p);
                sts32(sb + SM_LA + idx * 4, 0x80000000u);
                sts32(sb + SM_LB + idx * 4, 0x80000000u);
            }
        } else if (tid == 320) {
            sts32(sb + SM_FIRST + T * 4, 192u);
        }
    }
    slow = __syncthreads_or(slow);
    if (slow) {
        slow_path(sb, cta, x, ea, src, dst, w1);
        T = 0;
    }
    CSTAMP(8, tid == 0);

    if (wg == 2) {
        asm volatile("setmaxnreg.dec.sync.aligned.u32 72;");
        const char* xb = reinterpret_cast<const char*>(x) + (lane & 7) * 16;
        const char* eb = reinterpret_cast<const char*>(ea) + (lane & 1) * 16;
        const int xr0 = warp4 * 32 + (lane >> 3) * 8;
        const int er0 = warp4 * 32 + (lane >> 1);
        const uint32_t eoff = 16384 + er0 * 32 + (((lane & 1) ^ ((er0 >> 2) & 1)) << 4);
        const int orow = warp4 * 32 + lane;
        const uint32_t isw = ((orow >> 2) & 1) << 4;
        int ist = 0;
        for (int t = 0; t < T; t++) {
            const int st = t & 3;
            const uint32_t la = sb + SM_LA + t * 512, lb = sb + SM_LB + t * 512;
            const uint4 a0 = lds128(la + xr0 * 4), a1 = lds128(la + xr0 * 4 + 16);
            const uint32_t e0v = lds32(lb + er0 * 4), e1v = lds32(lb + er0 * 4 + 64);
            const uint32_t own = lds32(la + orow * 4);
            mbar_wait(sb + SM_BAR + 32 + st * 8, ((t >> 2) & 1) ^ 1);
            const uint32_t xs = sb + SM_XE + st * XE_ST;
            const uint32_t av[8] = {a0.x, a0.y, a0.z, a0.w, a1.x, a1.y, a1.z, a1.w};
#pragma unroll
            for (int i = 0; i < 8; i++)
                cp16z(xs + (xr0 + i) * 128 + (((lane & 7) ^ i) << 4), xb + (av[i] & 0x3FFFFFu), (int)av[i]);
            cp16z(xs + eoff, eb + (e0v & 0x7FFFFFFFu), (int)e0v);
            cp16z(xs + eoff + 512, eb + (e1v & 0x7FFFFFFFu), (int)e1v);
            mbar_cp_arrive(sb + SM_BAR + st * 8);
            const uint32_t sl = own >> 24;
            const uint32_t val = (sl & 1) ? 0x3F800000u : 0x00003F80u, wi = sl >> 1;
            const uint32_t ia = sb + SM_IND + ist * 4096 + orow * 32;
            sts128(ia + isw, wi == 0 ? val : 0u, wi == 1 ? val : 0u, wi == 2 ? val : 0u, wi == 3 ? val : 0u);
            sts128(ia + (isw ^ 16), wi == 4 ? val : 0u, wi == 5 ? val : 0u, wi == 6 ? val : 0u, wi == 7 ? val : 0u);
            fence_async();
            __syncwarp();
            if (lane == 0) mbar_arrive(sb + SM_BAR + st * 8);
            ist = (ist == 5) ? 0 : ist + 1;
        }
        asm volatile("cp.async.wait_all;" ::: "memory");
        tail_gemm(sb, wg, warp4, lane, cta, b2, out);
    } else {
        asm volatile("setmaxnreg.inc.sync.aligned.u32 216;");
        if (T > 0) {
            Cons c;
            c.sb = sb;
            c.lane = lane;
            c.q = lane & 3;
            c.slot_l = (lane & 7) + 8 * (lane >> 4);
            c.chunk_l = 2 * warp4 + ((lane >> 3) & 1);
            c.qa_l = sb + SM_QA + wg * 24576;
            c.fl_addr = c.qa_l + ((lane >> 2) & 3) * 4;
            c.fl_chunk = 2 * warp4 + (lane >> 4);
            uint32_t w1f[5][4];
#pragma unroll
            for (int ks = 0; ks < 5; ks++)
#pragma unroll
                for (int i = 0; i < 4; i++)
                    asm volatile("fma.rn.bf16x2 %0, %1, %2, %3;" : "=r"(w1f[ks][i]) : "r"(w1r[ks][i]), "r"(0x3F003F00u), "r"(0x80008000u));
            float a0[64], a1[64], agg[8];
            uint32_t pk[16];
#pragma unroll
            for (int i = 0; i < 8; i++) agg[i] = 0.f;
#pragma unroll
            for (int i = 0; i < 16; i++) pk[i] = 0u;
            int fcur = (int)lds32(sb + SM_FIRST), fprev = fcur, iprev = 0, icur = 0;
            {
                uint32_t qf[4];
                load_q(qf, c, fcur);
                mbar_wait(sb + SM_BAR, 0);
                fence_async();
                CSTAMP(9, tid == 0);
                wg_fence();
                issue_g1(a0, w1f, qf, sb, 0, 0);
                wg_wait<0>();
                fence_regs<64>(a0);
                if (lane == 0) mbar_arrive(sb + SM_BAR + 32);
            }
            int t = 0;
            while (true) {
                cons_step(a0, a1, agg, w1f, pk, c, t, T, iprev, icur, fprev, fcur);
                if (++t == T) break;
                cons_step(a1, a0, agg, w1f, pk, c, t, T, iprev, icur, fprev, fcur);
                if (++t == T) break;
            }
            wg_fence();
            issue_agg(agg, pk, sb, iprev);
            wg_wait<0>();
            fence_regs<8>(agg);
            flush_nodes(agg, c, fprev, 192);
        }
        CSTAMP(10, tid == 0);
        tail_gemm(sb, wg, warp4, lane, cta, b2, out);
        CSTAMP(11, tid == 0);
        TSTAMP(12, tid == 0);
    }
}

}

extern "C" void kernel_launch(void* const* d_in, const int* in_sizes, int n_in, void* d_out, int out_size) {
    (void)in_sizes; (void)n_in; (void)out_size;
    static int fused = -1;
    if (fused < 0) {
        int dev = 0, sms = 0, nb = 0;
        cudaGetDevice(&dev);
        cudaDeviceGetAttribute(&sms, cudaDevAttrMultiProcessorCount, dev);
        cudaFuncSetAttribute(mpnn_kernel, cudaFuncAttributeMaxDynamicSharedMemorySize, SM_TOTAL);
        cudaOccupancyMaxActiveBlocksPerMultiprocessor(&nb, mpnn_kernel, NT, SM_TOTAL);
        fused = (sms * nb >= G) ? 1 : 0;
    }
    const __nv_bfloat16* x  = (const __nv_bfloat16*)d_in[0];
    const __nv_bfloat16* ea = (const __nv_bfloat16*)d_in[1];
    const int* src = (const int*)d_in[2];
    const int* dst = (const int*)d_in[3];
    const __nv_bfloat16* w1 = (const __nv_bfloat16*)d_in[4];
    const __nv_bfloat16* b1 = (const __nv_bfloat16*)d_in[5];
    const __nv_bfloat16* w2 = (const __nv_bfloat16*)d_in[6];
    const __nv_bfloat16* b2 = (const __nv_bfloat16*)d_in[7];
    __nv_bfloat16* out = (__nv_bfloat16*)d_out;
    cudaStream_t s = cudaStreamPerThread;
    if (fused) {
        mpnn_kernel<<<G, NT, SM_TOTAL, s>>>(x, ea, src, dst, w1, b1, w2, b2, out, 3);
    } else {
        mpnn_kernel<<<G, NT, SM_TOTAL, s>>>(x, ea, src, dst, w1, b1, w2, b2, out, 1);
        mpnn_kernel<<<G, NT, SM_TOTAL, s>>>(x, ea, src, dst, w1, b1, w2, b2, out, 2);
    }
}
```

```cpp
#include <cuda_runtime.h>
#include <cuda_bf16.h>
#include <stdint.h>

namespace {

constexpr int NN   = 25000;
constexpr int NE   = 800000;
constexpr int G    = 132;
constexpr int NPB  = 190;
constexpr int NCH  = 128;
constexpr int CH   = 6256;
constexpr int RUNS = 96;
constexpr int RUNP = 98;
constexpr int CAPT = 52;
constexpr int CAP  = CAPT * 128;
constexpr int NT   = 640;
constexpr uint32_t CTR_WRAP = G * 0x7FFFFu - 1u;

constexpr int SM_XE   = 0;
constexpr int XE_ST   = 20480;
constexpr int SM_IND  = 81920;
constexpr int SM_QA   = 106496;
constexpr int SM_LB   = 155648;
constexpr int SM_LA   = SM_LB + CAP * 4;
constexpr int SM_W2   = SM_LA + CAP * 2;
constexpr int SM_MISC = SM_W2 + 16384;
constexpr int SM_CNT   = SM_MISC;
constexpr int SM_DEG   = SM_CNT + 640;
constexpr int SM_FLAG  = SM_DEG + 768;
constexpr int SM_BASE  = SM_FLAG + 32;
constexpr int SM_FIRST = SM_BASE + 768;
constexpr int SM_B1    = SM_FIRST + 256;
constexpr int SM_B2    = SM_B1 + 256;
constexpr int SM_BAR   = SM_B2 + 128;
constexpr int SM_TOTAL = SM_BAR + 64;
constexpr int F_TOT = SM_FLAG, F_DMAX = SM_FLAG + 4, F_BAD = SM_FLAG + 8, F_WMAX = SM_FLAG + 12, F_NF = SM_FLAG + 16,
              F_BIG = SM_FLAG + 20;
constexpr int SM_W1A  = 0;
constexpr int SM_W1B  = 20480;
constexpr int SM_XO   = 61440;
constexpr int SM_STG  = 86016;
constexpr int SM_SAGG = 0;
constexpr int SM_SQ   = NPB * 512;
static_assert(SM_STG + G * RUNP * 8 <= SM_W2 && SM_SQ * 2 <= SM_W2, "overlay");
static_assert(SM_TOTAL <= 232448, "smem");
static_assert(SM_W2 % 1024 == 0 && SM_QA % 1024 == 0 && SM_B1 % 16 == 0 && SM_BAR % 8 == 0, "align");

__device__ uint4 g_rec[G * NCH * RUNS / 2];
__device__ uint4 g_xh[(NN + 1) * 8];
__device__ unsigned g_ctr;
#define TSTAMP(i, cond)
#define CSTAMP(i, cond)

__device__ __forceinline__ uint64_t mkdesc(uint32_t addr, uint32_t lbo, uint32_t sbo, uint32_t swz) {
    return (uint64_t)((addr & 0x3FFFF) >> 4) | ((uint64_t)(lbo >> 4) << 16) | ((uint64_t)(sbo >> 4) << 32) |
           ((uint64_t)swz << 62);
}
__device__ __forceinline__ void wg_fence()  { asm volatile("wgmma.fence.sync.aligned;" ::: "memory"); }
__device__ __forceinline__ void wg_commit() { asm volatile("wgmma.commit_group.sync.aligned;" ::: "memory"); }
template <int N> __device__ __forceinline__ void wg_wait() { asm volatile("wgmma.wait_group.sync.aligned %0;" ::"n"(N) : "memory"); }
__device__ __forceinline__ void fence_async() { asm volatile("fence.proxy.async.shared::cta;" ::: "memory"); }

#define R8(d, o) "+f"(d[o + 0]), "+f"(d[o + 1]), "+f"(d[o + 2]), "+f"(d[o + 3]), "+f"(d[o + 4]), "+f"(d[o + 5]), "+f"(d[o + 6]), "+f"(d[o + 7])
#define W8(d, o) "=f"(d[o + 0]), "=f"(d[o + 1]), "=f"(d[o + 2]), "=f"(d[o + 3]), "=f"(d[o + 4]), "=f"(d[o + 5]), "=f"(d[o + 6]), "=f"(d[o + 7])
#define U8(d, o) "+r"(d[o + 0]), "+r"(d[o + 1]), "+r"(d[o + 2]), "+r"(d[o + 3]), "+r"(d[o + 4]), "+r"(d[o + 5]), "+r"(d[o + 6]), "+r"(d[o + 7])
#define V8(d, o) "=r"(d[o + 0]), "=r"(d[o + 1]), "=r"(d[o + 2]), "=r"(d[o + 3]), "=r"(d[o + 4]), "=r"(d[o + 5]), "=r"(d[o + 6]), "=r"(d[o + 7])
#define L32 "{%0,%1,%2,%3,%4,%5,%6,%7,%8,%9,%10,%11,%12,%13,%14,%15,%16,%17,%18,%19,%20,%21,%22,%23,%24,%25,%26,%27,%28,%29,%30,%31}"
#define L48 "{%0,%1,%2,%3,%4,%5,%6,%7,%8,%9,%10,%11,%12,%13,%14,%15,%16,%17,%18,%19,%20,%21,%22,%23,%24,%25,%26,%27,%28,%29,%30,%31,%32,%33,%34,%35,%36,%37,%38,%39,%40,%41,%42,%43,%44,%45,%46,%47}"

__device__ __forceinline__ void h128z(uint32_t* d, const uint32_t* a, uint64_t db) {
    asm volatile("{.reg .pred p; setp.ne.b32 p, 0, 0;\n"
                 "wgmma.mma_async.sync.aligned.m64n128k16.f16.f16.f16 " L32 ", {%32,%33,%34,%35}, %36, p, 1, 1, 0;}"
                 : V8(d, 0), V8(d, 8), V8(d, 16), V8(d, 24) : "r"(a[0]), "r"(a[1]), "r"(a[2]), "r"(a[3]), "l"(db));
}
__device__ __forceinline__ void h128(uint32_t* d, const uint32_t* a, uint64_t db) {
    asm volatile("{.reg .pred p; setp.eq.b32 p, 0, 0;\n"
                 "wgmma.mma_async.sync.aligned.m64n128k16.f16.f16.f16 " L32 ", {%32,%33,%34,%35}, %36, p, 1, 1, 0;}"
                 : U8(d, 0), U8(d, 8), U8(d, 16), U8(d, 24) : "r"(a[0]), "r"(a[1]), "r"(a[2]), "r"(a[3]), "l"(db));
}
__device__ __forceinline__ void r16t(float* d, const uint32_t* a, uint64_t db) {
    asm volatile("{.reg .pred p; setp.eq.b32 p, 0, 0;\n"
                 "wgmma.mma_async.sync.aligned.m64n16k16.f32.f16.f16 {%0,%1,%2,%3,%4,%5,%6,%7}, {%8,%9,%10,%11}, %12, p, 1, 1, 1;}"
                 : R8(d, 0) : "r"(a[0]), "r"(a[1]), "r"(a[2]), "r"(a[3]), "l"(db));
}
__device__ __forceinline__ void q_gemm(float* d, uint64_t da, uint64_t db) {
    asm volatile("{.reg .pred p, q; .reg .b64 a, b; setp.ne.b32 p, 0, 0; setp.eq.b32 q, 0, 0;\n"
                 "wgmma.fence.sync.aligned;\n"
                 "wgmma.mma_async.sync.aligned.m64n96k16.f32.bf16.bf16 " L48 ", %48, %49, p, 1, 1, 1, 0;\n"
                 "add.s64 a, %48, 128; add.s64 b, %49, 2;\n"
                 "wgmma.mma_async.sync.aligned.m64n96k16.f32.bf16.bf16 " L48 ", a, b, q, 1, 1, 1, 0;\n"
                 "add.s64 a, %48, 256; add.s64 b, %49, 4;\n"
                 "wgmma.mma_async.sync.aligned.m64n96k16.f32.bf16.bf16 " L48 ", a, b, q, 1, 1, 1, 0;\n"
                 "add.s64 a, %48, 384; add.s64 b, %49, 6;\n"
                 "wgmma.mma_async.sync.aligned.m64n96k16.f32.bf16.bf16 " L48 ", a, b, q, 1, 1, 1, 0;\n"
                 "wgmma.commit_group.sync.aligned;\n"
                 "wgmma.wait_group.sync.aligned 0;}"
                 : W8(d, 0), W8(d, 8), W8(d, 16), W8(d, 24), W8(d, 32), W8(d, 40)
                 : "l"(da), "l"(db) : "memory");
}
__device__ __forceinline__ void ss64t(float* d, uint64_t da, uint64_t db, int acc) {
    asm volatile("{.reg .pred p; setp.ne.b32 p, %34, 0;\n"
                 "wgmma.mma_async.sync.aligned.m64n64k16.f32.bf16.bf16 " L32 ", %32, %33, p, 1, 1, 0, 1;}"
                 : R8(d, 0), R8(d, 8), R8(d, 16), R8(d, 24)
                 : "l"(da), "l"(db), "r"(acc));
}
template <int NREG> __device__ __forceinline__ void fence_regs(float* d) {
#pragma unroll
    for (int i = 0; i < NREG; i++) asm volatile("" : "+f"(d[i])::"memory");
}
template <int NREG> __device__ __forceinline__ void fence_regs(uint32_t* d) {
#pragma unroll
    for (int i = 0; i < NREG; i++) asm volatile("" : "+r"(d[i])::"memory");
}
__device__ __forceinline__ void ldsm4t(uint32_t* r, uint32_t addr) {
    asm volatile("ldmatrix.sync.aligned.m8n8.x4.trans.shared.b16 {%0,%1,%2,%3}, [%4];"
                 : "=r"(r[0]), "=r"(r[1]), "=r"(r[2]), "=r"(r[3]) : "r"(addr) : "memory");
}
__device__ __forceinline__ void stsm4t(uint32_t addr, uint32_t a, uint32_t b, uint32_t c, uint32_t d) {
    asm volatile("stmatrix.sync.aligned.m8n8.x4.trans.shared.b16 [%0], {%1,%2,%3,%4};" ::"r"(addr), "r"(a), "r"(b), "r"(c), "r"(d) : "memory");
}
__device__ __forceinline__ void cp16(uint32_t s, const void* g) {
    asm volatile("cp.async.cg.shared.global [%0], [%1], 16;" ::"r"(s), "l"(g) : "memory");
}
__device__ __forceinline__ void cp4(uint32_t s, const void* g) {
    asm volatile("cp.async.ca.shared.global [%0], [%1], 4;" ::"r"(s), "l"(g) : "memory");
}
__device__ __forceinline__ void cp_wait_all() { asm volatile("cp.async.wait_all;" ::: "memory"); }
__device__ __forceinline__ void mbar_init(uint32_t a, int cnt) { asm volatile("mbarrier.init.shared::cta.b64 [%0], %1;" ::"r"(a), "r"(cnt) : "memory"); }
__device__ __forceinline__ void mbar_arrive(uint32_t a) { asm volatile("mbarrier.arrive.shared::cta.b64 _, [%0];" ::"r"(a) : "memory"); }
__device__ __forceinline__ void mbar_cp_arrive(uint32_t a) { asm volatile("cp.async.mbarrier.arrive.noinc.shared::cta.b64 [%0];" ::"r"(a) : "memory"); }
__device__ __forceinline__ void mbar_wait(uint32_t a, uint32_t parity) {
    asm volatile("{.reg .pred p; .reg .u32 n; mov.u32 n, 0;\n"
                 "MW_%=: mbarrier.try_wait.parity.shared::cta.b64 p, [%0], %1;\n"
                 "@p bra MD_%=;\n"
                 "add.u32 n, n, 1; setp.gt.u32 p, n, 0x100000;\n"
                 "@p trap;\n"
                 "bra MW_%=;\n"
                 "MD_%=: }" ::"r"(a), "r"(parity) : "memory");
}
template <int ID, int CNT> __device__ __forceinline__ void bar_sync()   { asm volatile("bar.sync %0, %1;" ::"n"(ID), "n"(CNT) : "memory"); }
template <int ID, int CNT> __device__ __forceinline__ void bar_arrive() { asm volatile("bar.arrive %0, %1;" ::"n"(ID), "n"(CNT) : "memory"); }
template <int ID> __device__ __forceinline__ bool bar_or(bool v) {
    uint32_t r;
    asm volatile("{.reg .pred p, q; setp.ne.u32 q, %1, 0; bar.red.or.pred p, %2, 640, q; selp.u32 %0, 1, 0, p;}"
                 : "=r"(r) : "r"((uint32_t)v), "n"(ID) : "memory");
    return r != 0;
}
__device__ __forceinline__ float tanh_fast(float x) { float y; asm("tanh.approx.f32 %0, %1;" : "=f"(y) : "f"(x)); return y; }
__device__ __forceinline__ uint32_t pack2(float lo, float hi) {
    uint32_t r; asm("cvt.rn.bf16x2.f32 %0, %1, %2;" : "=r"(r) : "f"(hi), "f"(lo)); return r;
}
__device__ __forceinline__ uint32_t pack2h(float lo, float hi) {
    uint32_t r; asm("cvt.rn.f16x2.f32 %0, %1, %2;" : "=r"(r) : "f"(hi), "f"(lo)); return r;
}
__device__ __forceinline__ float bf_lo(uint32_t v) { return __uint_as_float(v << 16); }
__device__ __forceinline__ float bf_hi(uint32_t v) { return __uint_as_float(v & 0xFFFF0000u); }
__device__ __forceinline__ uint32_t bf2h(uint32_t v) { return pack2h(bf_lo(v), bf_hi(v)); }
__device__ __forceinline__ uint32_t amax2(uint32_t a, uint32_t b) {
    uint32_t r; asm("max.NaN.xorsign.abs.bf16x2 %0, %1, %2;" : "=r"(r) : "r"(a), "r"(b)); return r;
}
__device__ __forceinline__ uint32_t amax_fin(uint32_t m) { return max(m & 0x7FFFu, (m >> 16) & 0x7FFFu); }
__device__ __forceinline__ uint32_t silu_h2(uint32_t h) {
    uint32_t t, s;
    asm("tanh.approx.f16x2 %0, %1;" : "=r"(t) : "r"(h));
    asm("fma.rn.f16x2 %0, %1, %2, %1;" : "=r"(s) : "r"(h), "r"(t));
    return s;
}
__device__ __forceinline__ uint32_t hadd2(uint32_t a, uint32_t b) { uint32_t s; asm("add.rn.f16x2 %0, %1, %2;" : "=r"(s) : "r"(a), "r"(b)); return s; }
__device__ __forceinline__ uint32_t lds32(uint32_t a) { uint32_t v; asm volatile("ld.shared.b32 %0, [%1];" : "=r"(v) : "r"(a) : "memory"); return v; }
__device__ __forceinline__ uint32_t lds16(uint32_t a) { uint32_t v; asm volatile("ld.shared.u16 %0, [%1];" : "=r"(v) : "r"(a) : "memory"); return v; }
__device__ __forceinline__ uint4 lds128(uint32_t a) {
    uint4 v; asm volatile("ld.shared.v4.b32 {%0,%1,%2,%3}, [%4];" : "=r"(v.x), "=r"(v.y), "=r"(v.z), "=r"(v.w) : "r"(a) : "memory"); return v;
}
__device__ __forceinline__ void sts16(uint32_t a, uint32_t v) { asm volatile("st.shared.u16 [%0], %1;" ::"r"(a), "r"(v) : "memory"); }
__device__ __forceinline__ void sts32(uint32_t a, uint32_t v) { asm volatile("st.shared.b32 [%0], %1;" ::"r"(a), "r"(v) : "memory"); }
__device__ __forceinline__ void sts64(uint32_t a, uint32_t x, uint32_t y) { asm volatile("st.shared.v2.b32 [%0], {%1,%2};" ::"r"(a), "r"(x), "r"(y) : "memory"); }
__device__ __forceinline__ void sts128(uint32_t a, uint32_t x, uint32_t y, uint32_t z, uint32_t w) {
    asm volatile("st.shared.v4.b32 [%0], {%1,%2,%3,%4};" ::"r"(a), "r"(x), "r"(y), "r"(z), "r"(w) : "memory");
}
__device__ __forceinline__ uint32_t atoms_inc(uint32_t a) {
    uint32_t v; asm volatile("atom.shared.add.u32 %0, [%1], 1;" : "=r"(v) : "r"(a) : "memory"); return v;
}
__device__ __forceinline__ void st_rec(uint4* p, uint4 v) {
    uint64_t a = (uint64_t)v.x | ((uint64_t)v.y << 32), b = (uint64_t)v.z | ((uint64_t)v.w << 32);
    asm volatile("st.relaxed.gpu.global.v2.b64 [%0], {%1,%2};" ::"l"(p), "l"(a), "l"(b) : "memory");
}
__device__ __forceinline__ uint4 ld_rec(const uint4* p) {
    uint64_t a, b;
    asm volatile("ld.relaxed.gpu.global.v2.b64 {%0,%1}, [%2];" : "=l"(a), "=l"(b) : "l"(p) : "memory");
    return make_uint4((uint32_t)a, (uint32_t)(a >> 32), (uint32_t)b, (uint32_t)(b >> 32));
}
__device__ __forceinline__ uint2 ld_rec1(const uint2* p) {
    uint64_t a;
    asm volatile("ld.relaxed.gpu.global.b64 %0, [%1];" : "=l"(a) : "l"(p) : "memory");
    return make_uint2((uint32_t)a, (uint32_t)(a >> 32));
}
__device__ __forceinline__ uint4 ld_stream(const void* p) {
    uint4 v;
    asm volatile("ld.global.nc.L1::no_allocate.v4.u32 {%0,%1,%2,%3}, [%4];" : "=r"(v.x), "=r"(v.y), "=r"(v.z), "=r"(v.w) : "l"(p));
    return v;
}
__device__ __forceinline__ void l2_prefetch(const void* p, uint32_t bytes) {
    asm volatile("cp.async.bulk.prefetch.L2.global [%0], %1;" ::"l"(p), "r"(bytes) : "memory");
}
__device__ __forceinline__ int col2pos(int c) { return (c & ~15) | ((c & 7) << 1) | ((c >> 3) & 1); }

struct Args {
    const __nv_bfloat16 *x, *ea;
    const int *src, *dst;
    const __nv_bfloat16 *w1, *b1, *w2, *b2;
    __nv_bfloat16* out;
};

__device__ __forceinline__ void rank4(uint32_t sb, const uint4& dv, uint4& sv, uint32_t* pos) {
    const uint32_t dd[4] = {dv.x, dv.y, dv.z, dv.w};
    uint32_t ss[4] = {sv.x, sv.y, sv.z, sv.w};
#pragma unroll
    for (int k = 0; k < 4; k++) {
        const uint32_t b = (dd[k] * 22076u) >> 22;
        const uint32_t r = atoms_inc(sb + SM_CNT + b * 4);
        pos[k] = b * RUNP + 1 + min(r, (uint32_t)(RUNS - 1));
        ss[k] |= (dd[k] - b * NPB) << 16;
    }
    sv = make_uint4(ss[0], ss[1], ss[2], ss[3]);
}
__device__ __forceinline__ void stage4(uint32_t sb, const uint4& sv, const uint32_t* pos, uint32_t w) {
    sts64(sb + SM_STG + pos[0] * 8, sv.x, w);
    sts64(sb + SM_STG + pos[1] * 8, sv.y, w + 1);
    sts64(sb + SM_STG + pos[2] * 8, sv.z, w + 2);
    sts64(sb + SM_STG + pos[3] * 8, sv.w, w + 3);
}
__device__ __forceinline__ void copy_out(uint32_t sb, int cta, int warp, int lane, uint32_t tag) {
    uint32_t n[7];
#pragma unroll
    for (int i = 0; i < 7; i++) n[i] = lds32(sb + SM_CNT + (warp + 20 * i) * 4);
#pragma unroll
    for (int i = 0; i < 7; i++) {
        const int b = warp + 20 * i;
        if (i < 6 || b < G) {
            const int lim = (min(n[i], (uint32_t)(RUNS - 1)) + 4) & ~3;
            uint4* gp = g_rec + (size_t)(b * NCH + cta) * (RUNS / 2) + lane;
            const uint32_t sa = sb + SM_STG + b * (RUNP * 8) + lane * 16;
            if (2 * lane < lim) {
                uint4 v = lds128(sa);
                if (lane == 0) { v.x = n[i]; v.y = tag << 13; }
                st_rec(gp, v);
            }
            if (lim > 64 && 64 + 2 * lane < lim) st_rec(gp + 32, lds128(sa + 512));
        }
    }
}
__device__ __forceinline__ void load_w2(uint32_t sb, int u, int nthr, const Args& a) {
    for (int i = u; i < 128 * 32; i += nthr) {
        const int kp = i >> 5, w = i & 31;
        const int k = (kp & ~15) | ((kp & 1) << 3) | ((kp >> 1) & 7);
        cp4(sb + SM_W2 + kp * 128 + (((w & 7) ^ (kp & 7)) << 4) + (w >> 3) * 4, a.w2 + k * 64 + w * 2);
    }
    if (u < 8) cp16(sb + SM_B2 + u * 16, a.b2 + u * 8);
    cp_wait_all();
}

__device__ __forceinline__ void tail_gemm(uint32_t sb, int wg, int warp4, int lane, int bucket, __nv_bfloat16* __restrict__ out) {
    const int g = lane >> 2, q = lane & 3;
    float d[32];
#pragma unroll
    for (int i = 0; i < 32; i++) d[i] = 0.f;
    wg_fence();
#pragma unroll
    for (int ks = 0; ks < 8; ks++)
        ss64t(d, mkdesc(sb + SM_QA + (ks >> 2) * 24576 + wg * 8192 + (ks & 3) * 32, 16, 1024, 1),
              mkdesc(sb + SM_W2 + ks * 2048, 16, 1024, 1), ks);
    wg_commit();
    const uint4 bb0 = lds128(sb + SM_B2 + q * 32), bb1 = lds128(sb + SM_B2 + q * 32 + 16);
    const int node0 = wg * 64 + warp4 * 16 + g;
    const uint32_t dg0 = lds32(sb + SM_DEG + node0 * 4), dg1 = lds32(sb + SM_DEG + node0 * 4 + 32);
    wg_wait<0>();
    fence_regs<32>(d);
    const uint32_t bw[8] = {bb0.x, bb0.y, bb0.z, bb0.w, bb1.x, bb1.y, bb1.z, bb1.w};
    uint32_t m = 0;
#pragma unroll
    for (int r = 0; r < 2; r++) {
        const int node = node0 + 8 * r;
        const int gn = bucket * NPB + node;
        const uint32_t dg = r ? dg1 : dg0;
        const float fd = (float)dg;
        uint32_t o[8];
#pragma unroll
        for (int j = 0; j < 8; j++) {
            const float v0 = fmaf(fd, bf_lo(bw[j]), d[4 * j + 2 * r]);
            const float v1 = fmaf(fd, bf_hi(bw[j]), d[4 * j + 2 * r + 1]);
            o[j] = dg ? pack2(v0, v1) : 0u;
            m = amax2(m, o[j]);
        }
        if (node < NPB && gn < NN) {
            uint4* op = reinterpret_cast<uint4*>(out + (size_t)gn * 64 + 16 * q);
            op[0] = make_uint4(o[0], o[1], o[2], o[3]);
            op[1] = make_uint4(o[4], o[5], o[6], o[7]);
        }
    }
    if (amax_fin(m) >= 0x7F80u) sts32(sb + F_NF, 1u);
}
__device__ __forceinline__ void tail_scan(uint32_t sb, int u) {
    uint32_t m = 0;
#pragma unroll
    for (int j = 0; j < 6; j++) {
        const int row = (u >> 3) + 32 * j;
        const uint32_t dg = lds32(sb + SM_DEG + row * 4);
        const uint4 a = lds128(sb + SM_QA + row * 128 + (u & 7) * 16), b = lds128(sb + SM_QA + 24576 + row * 128 + (u & 7) * 16);
        const uint32_t v = amax2(amax2(amax2(a.x, a.y), amax2(a.z, a.w)), amax2(amax2(b.x, b.y), amax2(b.z, b.w)));
        if (dg) m = amax2(m, v);
    }
    const float thr = (float)lds32(sb + F_DMAX) * (1.f / 32768.f) * fmaf(88.f, bf_lo(lds32(sb + F_WMAX)), 30.f);
    if (bf_lo(amax_fin(m)) >= thr) sts32(sb + F_BIG, 1u);
}
__device__ __forceinline__ bool tail_failed(uint32_t sb) {
    bar_sync<1, NT>();
    return lds32(sb + F_NF) != 0 || lds32(sb + F_BIG) == 0;
}

__device__ __forceinline__ void slow_path(uint32_t sb, int bucket, const Args& a) {
    const int tid = threadIdx.x, lane = tid & 31, j = tid & 127, wg = tid >> 7;
    bar_sync<0, NT>();
    load_w2(sb, tid, NT, a);
    for (int i = tid; i < NPB * 128; i += NT) sts32(sb + SM_SAGG + i * 4, 0u);
    if (tid < 192) sts32(sb + SM_DEG + tid * 4, 0u);
    const unsigned short* w1u = reinterpret_cast<const unsigned short*>(a.w1);
    {
        uint32_t w[32];
#pragma unroll
        for (int k = 0; k < 32; k++) w[k] = w1u[(64 + 2 * k) * 128 + j] | ((uint32_t)w1u[(65 + 2 * k) * 128 + j] << 16);
        const float bj = __bfloat162float(a.b1[j]);
        for (int node = wg; node < NPB && bucket * NPB + node < NN; node += 5) {
            const uint4* xr = reinterpret_cast<const uint4*>(a.x + (size_t)(bucket * NPB + node) * 64);
            float h = bj;
            fence_regs<32>(w);
#pragma unroll
            for (int k = 0; k < 8; k++) {
                const uint4 v = __ldg(xr + k);
                const uint32_t vv[4] = {v.x, v.y, v.z, v.w};
#pragma unroll
                for (int i = 0; i < 4; i++) {
                    h = fmaf(bf_lo(vv[i]), bf_lo(w[4 * k + i]), h);
                    h = fmaf(bf_hi(vv[i]), bf_hi(w[4 * k + i]), h);
                }
            }
            sts32(sb + SM_SQ + (node * 128 + j) * 4, __float_as_uint(h));
        }
    }
    uint32_t w[40];
#pragma unroll
    for (int k = 0; k < 40; k++) {
        const int r = k < 32 ? 2 * k : 2 * k + 64;
        w[k] = w1u[r * 128 + j] | ((uint32_t)w1u[(r + 1) * 128 + j] << 16);
    }
    bar_sync<0, NT>();
    for (int e0 = wg * 32; e0 < NE; e0 += 160) {
        const int dn = a.dst[e0 + lane] - bucket * NPB;
        unsigned m = __ballot_sync(0xFFFFFFFFu, dn >= 0 && dn < NPB);
        while (m) {
            const int l = __ffs(m) - 1;
            m &= m - 1;
            const int node = __shfl_sync(0xFFFFFFFFu, dn, l);
            const int e = e0 + l;
            const uint4* xr = reinterpret_cast<const uint4*>(a.x + (size_t)a.src[e] * 64);
            const uint4* er = reinterpret_cast<const uint4*>(a.ea + (size_t)e * 16);
            float h = __uint_as_float(lds32(sb + SM_SQ + (node * 128 + j) * 4));
            fence_regs<40>(w);
#pragma unroll
            for (int k = 0; k < 10; k++) {
                const uint4 v = (k < 8) ? __ldg(xr + k) : __ldg(er + (k - 8));
                const uint32_t vv[4] = {v.x, v.y, v.z, v.w};
#pragma unroll
                for (int i = 0; i < 4; i++) {
                    h = fmaf(bf_lo(vv[i]), bf_lo(w[4 * k + i]), h);
                    h = fmaf(bf_hi(vv[i]), bf_hi(w[4 * k + i]), h);
                }
            }
            h *= 0.5f;
            const float f = fmaf(h, tanh_fast(h), h);
            asm volatile("red.shared.add.f32 [%0], %1;" ::"r"(sb + SM_SAGG + (node * 128 + j) * 4), "f"(f) : "memory");
            if (j == 0) atoms_inc(sb + SM_DEG + node * 4);
        }
    }
    bar_sync<0, NT>();
    for (int i = tid; i < NPB * 64; i += NT) {
        const int node = i >> 6, pr = i & 63;
        const int hid = (pr >> 3) * 16 + (pr & 7);
        const float u = __uint_as_float(lds32(sb + SM_SAGG + (node * 128 + hid) * 4));
        const float v = __uint_as_float(lds32(sb + SM_SAGG + (node * 128 + hid + 8) * 4));
        const int ch = (pr & 31) >> 2;
        sts32(sb + SM_QA + (pr >> 5) * 24576 + node * 128 + ((ch ^ (node & 7)) << 4) + (pr & 3) * 4, pack2(u, v));
    }
    fence_async();
    bar_sync<0, NT>();
    if (wg < 3) tail_gemm(sb, wg, (tid >> 5) & 3, lane, bucket, a.out);
}

__device__ __forceinline__ uint32_t read_ctr() {
    uint32_t v;
    asm volatile("ld.relaxed.gpu.global.u32 %0, [%1];" : "=r"(v) : "l"(&g_ctr) : "memory");
    return v;
}

template <int MODE>
__device__ __forceinline__ bool producer(uint32_t sb, const Args& a) {
    const int tid = threadIdx.x, lane = tid & 31, warp = tid >> 5, warp4 = warp & 3, u = tid - 512;
    const int cta = blockIdx.x;
    const int e0 = cta * CH;
    const int nv = (MODE & 1) && cta < NCH ? min(CH, NE - e0) >> 2 : 0;
    const bool extra = 1536 + u < nv;
    uint4 dv, sv;
    if (extra) {
        dv = ld_stream(reinterpret_cast<const uint4*>(a.dst + e0) + 1536 + u);
        sv = ld_stream(reinterpret_cast<const uint4*>(a.src + e0) + 1536 + u);
    }
    const uint32_t ctr = MODE == 3 ? read_ctr() : 0u;
    if (u == 32) {
#pragma unroll
        for (int i = 0; i < 4; i++) {
            mbar_init(sb + SM_BAR + i * 8, 128 + 4);
            mbar_init(sb + SM_BAR + 32 + i * 8, 8);
        }
    }
    if (u == 64 && cta == G - 1) { l2_prefetch(a.w2, 16384); l2_prefetch(a.b2, 128); }
    bar_sync<0, NT>();
    const uint32_t epoch = ctr / G, tag = epoch + 1;
    uint4 xv[12];
    const int xrow = u >> 3;
    {
        const uint4* xp = reinterpret_cast<const uint4*>(a.x) + (size_t)(cta * NPB + xrow) * 8 + (u & 7) + (ctr >> 31);
#pragma unroll
        for (int j = 0; j < 12; j++) {
            const int r = xrow + 16 * j;
            xv[j] = make_uint4(0u, 0u, 0u, 0u);
            if (r < NPB && cta * NPB + r < NN) xv[j] = ld_stream(xp + j * 128);
        }
    }
    if (extra) {
        uint32_t pos[4];
        rank4(sb, dv, sv, pos);
        stage4(sb, sv, pos, (tag << 13) | ((1536 + u) * 4));
    }
    bar_sync<0, NT>();
    if (nv) copy_out(sb, cta, warp, lane, tag);
    {
        uint4* hp = g_xh + (size_t)(cta * NPB + xrow) * 8 + (u & 7);
        const uint32_t xa = sb + SM_XO + xrow * 128 + (((u & 7) ^ (xrow & 7)) << 4);
#pragma unroll
        for (int j = 0; j < 12; j++) {
            const int r = xrow + 16 * j;
            if (MODE & 2) sts128(xa + j * 2048, xv[j].x, xv[j].y, xv[j].z, xv[j].w);
            if ((MODE & 1) && r < NPB && cta * NPB + r <= NN)
                hp[j * 128] = make_uint4(bf2h(xv[j].x), bf2h(xv[j].y), bf2h(xv[j].z), bf2h(xv[j].w));
        }
    }
    if (!(MODE & 2)) return false;
    fence_async();
    bar_sync<0, NT>();
    bool slow = false;
    int T = 0;
    if (warp == 19) {
        if (MODE == 3 && lane == 0) {
            asm volatile("fence.acq_rel.gpu;" ::: "memory");
            asm volatile("red.relaxed.gpu.global.inc.u32 [%0], %1;" ::"l"(&g_ctr), "r"(CTR_WRAP) : "memory");
            int it = 0;
            while (read_ctr() - epoch * G < (uint32_t)G)
                if (++it > (1 << 22)) __trap();
            asm volatile("fence.acq_rel.gpu;" ::: "memory");
        }
        __syncwarp();
        CSTAMP(13, lane == 0);
    } else {
        if (u < 80) {
            uint32_t m = 0;
#pragma unroll
            for (int c = 0; c < 16; c++) {
                const uint4 v = lds128(sb + SM_W1A + (c >> 3) * 10240 + u * 128 + (((c & 7) ^ (u & 7)) << 4));
                m = amax2(m, amax2(amax2(v.x, v.y), amax2(v.z, v.w)));
            }
            m = amax_fin(m);
            if (m != 0 && m < 0x3A00u) sts32(sb + F_BAD, 1u);
            asm volatile("red.shared.max.u32 [%0], %1;" ::"r"(sb + F_WMAX), "r"(m) : "memory");
        }
        __syncwarp();
        if (warp == 16) {
            bar_sync<3, 544>();
            uint32_t v[6], s = 0, dm = 0;
#pragma unroll
            for (int k = 0; k < 6; k++) {
                const uint32_t dg = lds32(sb + SM_DEG + (lane * 6 + k) * 4);
                v[k] = s;
                s += (dg + 1) & ~1u;
                dm = max(dm, dg);
            }
            uint32_t inc = s;
#pragma unroll
            for (int o = 1; o < 32; o <<= 1) {
                const uint32_t w = __shfl_up_sync(0xFFFFFFFFu, inc, o);
                if (lane >= o) inc += w;
            }
#pragma unroll
            for (int k = 0; k < 6; k++) sts32(sb + SM_BASE + (lane * 6 + k) * 4, inc - s + v[k]);
            dm = __reduce_max_sync(0xFFFFFFFFu, dm);
            if (lane == 31) sts64(sb + F_TOT, inc, dm);
        }
        bar_sync<4, 608>();
        const int total = (int)lds32(sb + F_TOT);
        slow = lds32(sb + F_BAD) != 0 || total > CAP || lds32(sb + F_DMAX) > 255u;
        if (!slow) {
            T = (total + 127) >> 7;
#pragma unroll
            for (int k = 0; k < 2; k++) {
                const int n = u + 96 * k;
                const int dg = (int)lds32(sb + SM_DEG + n * 4), b0 = (int)lds32(sb + SM_BASE + n * 4);
                if (dg & 1) {
                    sts16(sb + SM_LA + (b0 + dg) * 2, NN);
                    sts32(sb + SM_LB + (b0 + dg) * 4, 16u);
                }
                for (int t = (b0 + 127) >> 7; t * 128 < b0 + dg; t++) sts32(sb + SM_FIRST + t * 4, n);
                if (dg > 0 && n >= 15 && (int)lds32(sb + SM_BASE + (n - 15) * 4) > (b0 & ~127)) slow = true;
                const int p = total + n;
                if (p < T * 128) {
                    sts16(sb + SM_LA + p * 2, NN);
                    sts32(sb + SM_LB + p * 4, 16u);
                }
            }
            if (u == 0) sts32(sb + SM_FIRST + T * 4, NPB);
        }
    }
    slow = bar_or<5>(slow);
    if (slow) return true;
    asm volatile("setmaxnreg.dec.sync.aligned.u32 64;");
    T = ((int)lds32(sb + F_TOT) + 127) >> 7;
    const int T0 = (T + 1) >> 1;

    const char* xb = reinterpret_cast<const char*>(g_xh) + (lane & 7) * 16;
    const char* eb = reinterpret_cast<const char*>(a.ea) + (lane & 1) * 16;
    const int xp0 = warp4 * 32 + (lane >> 3) * 8;
    uint32_t xoff[4];
#pragma unroll
    for (int i = 0; i < 4; i++) {
        const int c = (xp0 & ~15) + ((xp0 & 8) >> 1) + i;
        xoff[i] = sb + SM_XE + c * 128 + (((lane & 7) ^ (c & 7)) << 4);
    }
    const int ec = warp4 * 32 + (lane >> 1);
    const uint32_t eoff = sb + SM_XE + 16384 + ec * 32 + (((lane & 1) ^ ((ec >> 2) & 1)) << 4);
    const uint32_t elist = sb + SM_LB + col2pos(ec) * 4;
    const int oc = warp4 * 32 + lane;
    const uint32_t ilist = sb + SM_LB + col2pos(oc) * 4;
    const uint32_t ioff = sb + SM_IND + oc * 32 + (((oc >> 2) & 1) << 4);
    uint4 ev[2][2];
    auto load_e = [&](uint4* v, int t, bool on) {
        const uint32_t l0 = lds32(elist + t * 512), l1 = lds32(elist + t * 512 + 64);
        v[0] = make_uint4(0u, 0u, 0u, 0u);
        v[1] = make_uint4(0u, 0u, 0u, 0u);
        if (on && !(l0 & 16)) v[0] = ld_stream(eb + (l0 & ~31u));
        if (on && !(l1 & 16)) v[1] = ld_stream(eb + (l1 & ~31u));
    };
    load_e(ev[0], 0, 0 < T);
    load_e(ev[1], T0, 1 < T);
    int i3 = 0;
    for (int k = 0; k < T0; k++) {
        if (k == 1) bar_sync<6, NT>();
#pragma unroll
        for (int s = 0; s < 2; s++) {
            if (s == 1 && 2 * k + 1 >= T) break;
            const int t = s * T0 + k, st = 2 * s + (k & 1);
            const uint4 la = lds128(sb + SM_LA + t * 256 + xp0 * 2);
            const uint32_t own = lds32(ilist + t * 512);
            const uint32_t ef[8] = {bf2h(ev[s][0].x), bf2h(ev[s][0].y), bf2h(ev[s][0].z), bf2h(ev[s][0].w),
                                    bf2h(ev[s][1].x), bf2h(ev[s][1].y), bf2h(ev[s][1].z), bf2h(ev[s][1].w)};
            load_e(ev[s], t + 1, 2 * k + s + 2 < T);
            const uint32_t val = (own & 1) ? 0x3C000000u : 0x00003C00u, wi = (own >> 1) & 15;
            mbar_wait(sb + SM_BAR + 32 + st * 8, ((k >> 1) & 1) ^ 1);
            const uint32_t so = st * XE_ST;
            const uint32_t lw[4] = {la.x, la.y, la.z, la.w};
#pragma unroll
            for (int i = 0; i < 4; i++) {
                cp16(xoff[i] + so, xb + (lw[i] & 0xFFFFu) * 128u);
                cp16(xoff[i] + so + 1024, xb + (lw[i] >> 16) * 128u);
            }
            mbar_cp_arrive(sb + SM_BAR + st * 8);
            sts128(eoff + so, ef[0], ef[1], ef[2], ef[3]);
            sts128(eoff + so + 512, ef[4], ef[5], ef[6], ef[7]);
            const uint32_t ia = ioff + (3 * s + i3) * 4096;
            sts128(ia, wi == 0 ? val : 0u, wi == 1 ? val : 0u, wi == 2 ? val : 0u, wi == 3 ? val : 0u);
            sts128(ia ^ 16, wi == 4 ? val : 0u, wi == 5 ? val : 0u, wi == 6 ? val : 0u, wi == 7 ? val : 0u);
            fence_async();
            __syncwarp();
            if (lane == 0) mbar_arrive(sb + SM_BAR + st * 8);
        }
        i3 = (i3 == 2) ? 0 : i3 + 1;
    }
    if (T0 < 2) bar_sync<6, NT>();
    load_w2(sb, u, 128, a);
    fence_async();
    bar_sync<1, NT>();
    tail_scan(sb, u + 128);
    if (!tail_failed(sb) || T == 0) return false;
    asm volatile("setmaxnreg.inc.sync.aligned.u32 96;");
    return true;
}

template <int MODE>
__device__ __forceinline__ bool consumer(uint32_t sb, const Args& a) {
    const int tid = threadIdx.x, lane = tid & 31, warp = tid >> 5, wg = tid >> 7, warp4 = warp & 3;
    const int cta = blockIdx.x;
    const int e0 = cta * CH;
    const int nv = (MODE & 1) && cta < NCH ? min(CH, NE - e0) >> 2 : 0;
    uint4 dv[3], sv[3];
#pragma unroll
    for (int j = 0; j < 3; j++)
        if (tid + 512 * j < nv) dv[j] = ld_stream(reinterpret_cast<const uint4*>(a.dst + e0) + tid + 512 * j);
#pragma unroll
    for (int j = 0; j < 3; j++)
        if (tid + 512 * j < nv) sv[j] = ld_stream(reinterpret_cast<const uint4*>(a.src + e0) + tid + 512 * j);
    const uint32_t ctr = MODE == 3 ? read_ctr() : 0u;
    if (tid < 360) sts32(sb + SM_CNT + tid * 4, 0u);
    if (MODE & 2) {
        const int r = tid >> 4, c = tid & 15;
        const uint32_t sw = r * 128 + (((c & 7) ^ (r & 7)) << 4);
        const __nv_bfloat16* wp = a.w1 + tid * 8;
        cp16(sb + SM_W1A + (c >> 3) * 10240 + sw, wp);
        cp16(sb + SM_W1A + (c >> 3) * 10240 + sw + 4096, wp + 4096);
        cp16(sb + SM_W1B + (c >> 3) * 8192 + sw, wp + 8192);
        cp16(sb + SM_W1B + (c >> 3) * 8192 + sw + 4096, wp + 12288);
        if (tid < 256) cp16(sb + SM_W1A + (c >> 3) * 10240 + sw + 8192, wp + 16384);
        else if (tid < 272) cp16(sb + SM_B1 + (tid - 256) * 16, a.b1 + (tid - 256) * 8);
    }
    bar_sync<0, NT>();
    CSTAMP(2, tid == 0);
    const uint32_t tag = ctr / G + 1;
    {
        uint32_t pos[12];
#pragma unroll
        for (int j = 0; j < 3; j++)
            if (tid + 512 * j < nv) rank4(sb, dv[j], sv[j], pos + 4 * j);
#pragma unroll
        for (int j = 0; j < 3; j++)
            if (tid + 512 * j < nv) stage4(sb, sv[j], pos + 4 * j, (tag << 13) | ((tid + 512 * j) * 4));
    }
    CSTAMP(3, tid == 0);
    bar_sync<0, NT>();
    if (nv) {
        copy_out(sb, cta, warp, lane, tag);
    }
    if (!(MODE & 2)) return false;
    CSTAMP(4, tid == 0);
    cp_wait_all();
    fence_async();
    bar_sync<0, NT>();
    CSTAMP(5, tid == 0);
    const int s = wg >> 1, h = wg & 1;
    const uint4* gp = g_rec + (size_t)(cta * NCH + warp * 8) * (RUNS / 2);
    uint2 hd = make_uint2(0u, tag << 13);
    if (lane < 8) hd = ld_rec1(reinterpret_cast<const uint2*>(gp + lane * (RUNS / 2)));

    {
        float d[48];
        const float ba = 0.5f * bf_lo(lds16(sb + SM_B1 + (h * 64 + warp4 * 16 + (lane >> 2)) * 2));
        const float bb = 0.5f * bf_lo(lds16(sb + SM_B1 + (h * 64 + warp4 * 16 + (lane >> 2)) * 2 + 16));
        q_gemm(d, mkdesc(sb + SM_W1B + h * 8192, 16, 1024, 1), mkdesc(sb + SM_XO + s * 12288, 16, 1024, 1));
        const uint32_t qa = sb + SM_QA + h * 24576 + (s * 96 + (lane >> 4) * 8 + (lane & 7)) * 128 +
                            (((2 * warp4 + ((lane >> 3) & 1)) ^ (lane & 7)) << 4);
#pragma unroll
        for (int j = 0; j < 6; j++) {
            const float* e = d + 8 * j;
            stsm4t(qa + j * 2048, pack2h(fmaf(e[0], 0.5f, ba), fmaf(e[1], 0.5f, ba)), pack2h(fmaf(e[2], 0.5f, bb), fmaf(e[3], 0.5f, bb)),
                   pack2h(fmaf(e[4], 0.5f, ba), fmaf(e[5], 0.5f, ba)), pack2h(fmaf(e[6], 0.5f, bb), fmaf(e[7], 0.5f, bb)));
        }
    }
    CSTAMP(6, tid == 0);

    if (MODE == 3) {
        int it = 0;
        while (!__all_sync(0xFFFFFFFFu, (hd.y >> 13) == tag)) {
            if (++it > (1 << 22)) __trap();
            if (lane < 8) hd = ld_rec1(reinterpret_cast<const uint2*>(gp + lane * (RUNS / 2)));
        }
    }
    if (hd.x > RUNS - 1) { sts32(sb + F_BAD, 1u); hd.x = 0; }
    CSTAMP(7, tid == 0);
    uint4 rv[8];
    uint2 rx[8];
    uint32_t n[8];
#pragma unroll
    for (int i = 0; i < 8; i++) {
        n[i] = __shfl_sync(0xFFFFFFFFu, hd.x, i);
        if (2 * lane <= n[i]) rv[i] = ld_rec(gp + i * (RUNS / 2) + lane);
    }
    const bool anyx = __any_sync(0xFFFFFFFFu, hd.x > 63);
    if (anyx) {
#pragma unroll
        for (int i = 0; i < 8; i++)
            if (64 + lane <= n[i]) rx[i] = ld_rec1(reinterpret_cast<const uint2*>(gp + i * (RUNS / 2) + 32) + lane);
    }
    uint32_t w1f[5][4];
    {
        const int kr = (lane & 7) + 8 * (lane >> 4), ch = 2 * warp4 + ((lane >> 3) & 1);
#pragma unroll
        for (int ks = 0; ks < 5; ks++) {
            ldsm4t(w1f[ks], sb + SM_W1A + h * 10240 + (16 * ks + kr) * 128 + ((ch ^ (kr & 7)) << 4));
#pragma unroll
            for (int i = 0; i < 4; i++) w1f[ks][i] = pack2h(0.5f * bf_lo(w1f[ks][i]), 0.5f * bf_hi(w1f[ks][i]));
        }
    }
#pragma unroll
    for (int i = 0; i < 8; i++) {
        const bool v0 = 2 * lane <= n[i] && lane > 0, v1 = 2 * lane + 1 <= n[i];
        if (MODE == 3) {
            int it = 0;
            while ((v0 && (rv[i].y >> 13) != tag) || (v1 && (rv[i].w >> 13) != tag)) {
                if (++it > (1 << 22)) __trap();
                rv[i] = ld_rec(gp + i * (RUNS / 2) + lane);
            }
        }
        if (v0) rv[i].x += atoms_inc(sb + SM_DEG + (rv[i].x >> 16) * 4) << 24; else rv[i].x = 0xFFFFFFFFu;
        if (v1) rv[i].z += atoms_inc(sb + SM_DEG + (rv[i].z >> 16) * 4) << 24; else rv[i].z = 0xFFFFFFFFu;
    }
    if (anyx) {
#pragma unroll
        for (int i = 0; i < 8; i++) {
            const bool v0 = 64 + lane <= n[i];
            if (MODE == 3) {
                int it = 0;
                while (v0 && (rx[i].y >> 13) != tag) {
                    if (++it > (1 << 22)) __trap();
                    rx[i] = ld_rec1(reinterpret_cast<const uint2*>(gp + i * (RUNS / 2) + 32) + lane);
                }
            }
            if (v0) rx[i].x += atoms_inc(sb + SM_DEG + (rx[i].x >> 16) * 4) << 24; else rx[i].x = 0xFFFFFFFFu;
        }
    }
    __syncwarp();
    CSTAMP(8, tid == 0);
    bar_arrive<3, 544>();
    bar_sync<4, 608>();
    const int total = (int)lds32(sb + F_TOT);
    bool slow = lds32(sb + F_BAD) != 0 || total > CAP || lds32(sb + F_DMAX) > 255u;
    const int T = (total + 127) >> 7, T0 = (T + 1) >> 1;
    auto locate = [&](uint32_t& ra, uint32_t& rb, int i) {
        if (ra != 0xFFFFFFFFu) {
            const uint32_t node = (ra >> 16) & 255u;
            const uint32_t p = lds32(sb + SM_BASE + node * 4) + (ra >> 24);
            rb = ((rb & 0x1FFFu) + (warp * 8 + i) * CH) * 32u + (node & 15u);
            ra = (ra & 0xFFFFu) | (p << 16);
        }
    };
    auto place = [&](uint32_t ra, uint32_t rb, bool head) {
        const uint32_t p = ra >> 16;
        const bool early = p < 256u || p - T0 * 128u < 256u;
        if (ra != 0xFFFFFFFFu && early == head) {
            sts16(sb + SM_LA + p * 2, ra);
            sts32(sb + SM_LB + p * 4, rb);
        }
    };
    if (!slow) {
#pragma unroll
        for (int i = 0; i < 8; i++) { locate(rv[i].x, rv[i].y, i); locate(rv[i].z, rv[i].w, i); }
#pragma unroll
        for (int i = 0; i < 8; i++) { place(rv[i].x, rv[i].y, true); place(rv[i].z, rv[i].w, true); }
        if (anyx) {
#pragma unroll
            for (int i = 0; i < 8; i++) { locate(rx[i].x, rx[i].y, i); place(rx[i].x, rx[i].y, true); place(rx[i].x, rx[i].y, false); }
        }
    }
    __syncwarp();
    slow = bar_or<5>(slow);
    if (slow) return true;
    CSTAMP(14, tid == 0);
#pragma unroll
    for (int i = 0; i < 8; i++) { place(rv[i].x, rv[i].y, false); place(rv[i].z, rv[i].w, false); }
    __syncwarp();
    bar_arrive<6, NT>();
    asm volatile("setmaxnreg.inc.sync.aligned.u32 104;");

    const int Ts = s ? T - T0 : T0;
    if (Ts > 0) {
        const int q = lane & 3;
        const uint32_t qa_l = sb + SM_QA + h * 24576;
        const int slot_l = (lane & 7) + 8 * (lane >> 4), chunk_l = 2 * warp4 + ((lane >> 3) & 1);
        const uint32_t fl_addr = qa_l + ((lane >> 2) & 3) * 4;
        const int fl_chunk = 2 * warp4 + (lane >> 4);
        const uint32_t fa = sb + SM_FIRST + s * T0 * 4;
        const int fb = (int)lds32(sb + SM_FIRST + T0 * 4);
        const int fbx = s ? fb : -1;
        uint32_t acc[32], pk[16];
        float agg[8];
#pragma unroll
        for (int i = 0; i < 8; i++) agg[i] = 0.f;
#pragma unroll
        for (int i = 0; i < 16; i++) pk[i] = 0u;
        auto flush = [&](int f0, int f1) {
#pragma unroll
            for (int j = 0; j < 4; j++) {
                const int sl = 2 * q + (j & 1) + 8 * (j >> 1);
                const int node = f0 + ((sl - f0) & 15);
                const int i0 = (j >> 1) * 4 + (j & 1);
                if (node < f1) {
                    const int row = node == fbx ? NPB : node;
                    sts32(fl_addr + row * 128 + ((fl_chunk ^ (row & 7)) << 4), pack2(agg[i0], agg[i0 + 2]));
                    agg[i0] = 0.f;
                    agg[i0 + 2] = 0.f;
                }
            }
        };
        int fcur = (int)lds32(fa), fprev = fcur;
        uint32_t iprev = sb + SM_IND + 3 * s * 4096, icur = iprev;
        const uint32_t ilast = iprev + 2 * 4096;
        mbar_wait(sb + SM_BAR + 2 * s * 8, 0);
        CSTAMP(9, tid == 0);
        for (int k = 0; k < Ts; k++) {
            const int st = 2 * s + (k & 1);
            const uint64_t dx = mkdesc(sb + SM_XE + st * XE_ST, 16, 1024, 1);
            const uint64_t de = mkdesc(sb + SM_XE + st * XE_ST + 16384, 16, 256, 3);
            const uint64_t da = mkdesc(iprev, 16, 512, 3);
            wg_fence();
#pragma unroll
            for (int kk = 0; kk < 4; kk++) r16t(agg, pk + 4 * kk, da + kk * 64);
            wg_commit();
            h128z(acc, w1f[0], dx);
            h128(acc, w1f[1], dx + 2);
            h128(acc, w1f[2], dx + 4);
            h128(acc, w1f[3], dx + 6);
            h128(acc, w1f[4], de);
            wg_commit();
            const int qn = min(fcur + ((slot_l - fcur) & 15), 191);
            const uint32_t qaddr = qa_l + qn * 128 + ((chunk_l ^ (qn & 7)) << 4);
            const int fnext = (int)lds32(fa + (k + 1) * 4);
            wg_wait<1>();
            fence_regs<8>(agg);
            fence_regs<16>(pk);
            uint32_t qf[4];
            ldsm4t(qf, qaddr);
            fence_regs<4>(qf);
            wg_fence();
            h128(acc, qf, mkdesc(icur, 16, 256, 3));
            wg_commit();
            flush(fprev, fcur);
            wg_wait<0>();
            fence_regs<32>(acc);
            if (lane == 0) mbar_arrive(sb + SM_BAR + 32 + st * 8);
#pragma unroll
            for (int i = 0; i < 16; i++) {
                const int i0 = (i >> 1) * 4 + (i & 1);
                pk[i] = hadd2(silu_h2(acc[i0]), silu_h2(acc[i0 + 2]));
            }
            fence_regs<16>(pk);
            iprev = icur;
            icur = icur == ilast ? ilast - 2 * 4096 : icur + 4096;
            fprev = fcur;
            fcur = fnext;
            if (k + 1 < Ts) mbar_wait(sb + SM_BAR + (st ^ 1) * 8, ((k + 1) >> 1) & 1);
        }
        const uint64_t da = mkdesc(iprev, 16, 512, 3);
        wg_fence();
#pragma unroll
        for (int kk = 0; kk < 4; kk++) r16t(agg, pk + 4 * kk, da + kk * 64);
        wg_commit();
        wg_wait<0>();
        fence_regs<8>(agg);
        flush(fprev, fcur);
        if (fb < NPB) {
            if (s) {
                if (h) bar_arrive<8, 256>(); else bar_arrive<7, 256>();
            } else {
                if (h) bar_sync<8, 256>(); else bar_sync<7, 256>();
#pragma unroll
                for (int j = 0; j < 4; j++) {
                    const int i0 = (j >> 1) * 4 + (j & 1);
                    if (2 * q + (j & 1) + 8 * (j >> 1) == (fb & 15)) {
                        const uint32_t v = lds32(fl_addr + NPB * 128 + ((fl_chunk ^ (NPB & 7)) << 4));
                        sts32(fl_addr + fb * 128 + ((fl_chunk ^ (fb & 7)) << 4), pack2(agg[i0] + bf_lo(v), agg[i0 + 2] + bf_hi(v)));
                    }
                }
            }
        }
    }
    CSTAMP(10, tid == 0);
    fence_async();
    bar_sync<1, NT>();
    if (wg < 3) tail_gemm(sb, wg, warp4, lane, cta, a.out);
    else tail_scan(sb, tid - 384);
    CSTAMP(15, tid == 0);
    if (!tail_failed(sb) || T == 0) return false;
    asm volatile("setmaxnreg.dec.sync.aligned.u32 96;");
    return true;
}

template <int MODE>
__global__ void __launch_bounds__(NT, 1) mpnn_kernel(const __grid_constant__ Args a) {
    extern __shared__ __align__(1024) uint8_t smem[];
    const uint32_t sb = (uint32_t)__cvta_generic_to_shared(smem);
    TSTAMP(0, threadIdx.x == 0);
    CSTAMP(1, threadIdx.x == 0);
    const bool slow = threadIdx.x >= 512 ? producer<MODE>(sb, a) : consumer<MODE>(sb, a);
    if ((MODE & 2) && slow) slow_path(sb, blockIdx.x, a);
    CSTAMP(11, threadIdx.x == 0);
    TSTAMP(12, threadIdx.x == 0);
}

}

extern "C" void kernel_launch(void* const* d_in, const int* in_sizes, int n_in, void* d_out, int out_size) {
    (void)in_sizes; (void)n_in; (void)out_size;
    static int fused = -1;
    if (fused < 0) {
        int dev = 0, sms = 0, nb = 0;
        cudaGetDevice(&dev);
        cudaDeviceGetAttribute(&sms, cudaDevAttrMultiProcessorCount, dev);
        cudaFuncSetAttribute(mpnn_kernel<1>, cudaFuncAttributeMaxDynamicSharedMemorySize, SM_TOTAL);
        cudaFuncSetAttribute(mpnn_kernel<2>, cudaFuncAttributeMaxDynamicSharedMemorySize, SM_TOTAL);
        cudaFuncSetAttribute(mpnn_kernel<3>, cudaFuncAttributeMaxDynamicSharedMemorySize, SM_TOTAL);
        cudaOccupancyMaxActiveBlocksPerMultiprocessor(&nb, mpnn_kernel<3>, NT, SM_TOTAL);
        fused = (sms * nb >= G) ? 1 : 0;
    }
    Args a;
    a.x   = (const __nv_bfloat16*)d_in[0];
    a.ea  = (const __nv_bfloat16*)d_in[1];
    a.src = (const int*)d_in[2];
    a.dst = (const int*)d_in[3];
    a.w1  = (const __nv_bfloat16*)d_in[4];
    a.b1  = (const __nv_bfloat16*)d_in[5];
    a.w2  = (const __nv_bfloat16*)d_in[6];
    a.b2  = (const __nv_bfloat16*)d_in[7];
    a.out = (__nv_bfloat16*)d_out;
    cudaStream_t s = cudaStreamPerThread;
    if (fused) {
        mpnn_kernel<3><<<G, NT, SM_TOTAL, s>>>(a);
    } else {
        mpnn_kernel<1><<<G, NT, SM_TOTAL, s>>>(a);
        mpnn_kernel<2><<<G, NT, SM_TOTAL, s>>>(a);
    }
}
```

```cpp
#include <cuda_runtime.h>
#include <cuda_bf16.h>
#include <stdint.h>

namespace {

constexpr int NN   = 25000;
constexpr int NE   = 800000;
constexpr int G    = 132;
constexpr int NPB  = 190;
constexpr int NCH  = 128;
constexpr int CH   = 6256;
constexpr int CAPT = 52;
constexpr int CAP  = CAPT * 128;
constexpr int NT   = 640;
constexpr int XCAP = 512;
constexpr uint32_t CTR_WRAP = G * 0x80000u - 1u;
constexpr uint32_t TAGM = 511u << 13, PADW = 0x800000u, BADH = 0x7FFFFFFFu;

constexpr int SM_CNT  = 0;
constexpr int SM_DEG  = 576;
constexpr int SM_FLAG = SM_DEG + 768;
constexpr int SM_BASE = SM_FLAG + 32;
constexpr int SM_TT   = SM_BASE + 768;
constexpr int SM_XB   = SM_TT + 1024;
constexpr int SM_B1   = SM_XB + 512;
constexpr int SM_B2   = SM_B1 + 256;
constexpr int SM_BAR  = SM_B2 + 128;
constexpr int SM_XE   = 5120;
constexpr int XE_S    = 20480, XE_P = 65536;
constexpr int SM_IND  = SM_XE + 2 * XE_S;
constexpr int SM_RAW  = 126976;
constexpr int SM_QA   = SM_RAW + 16384;
constexpr int SM_LB   = SM_QA + 49152;
constexpr int SM_LA   = SM_LB + CAP * 4;
constexpr int SM_TOTAL = SM_LA + CAP * 2;
constexpr int F_TOT = SM_FLAG, F_DMAX = SM_FLAG + 4, F_BAD = SM_FLAG + 8, F_WMAX = SM_FLAG + 12, F_NF = SM_FLAG + 16,
              F_BIG = SM_FLAG + 20, F_TAG = SM_FLAG + 24, F_XC = SM_FLAG + 28;
constexpr int SM_W1B  = SM_IND + 8192;
constexpr int SM_XO   = SM_W1B + 16384;
constexpr int SM_W1A  = SM_XO + 24576;
constexpr int RA = 400, RB = RA / 2;
constexpr int SM_STA  = SM_W1A + 20480;
constexpr int SM_STB  = SM_STA + G * RA;
constexpr int SM_DST  = 4224;
constexpr int SM_XR   = SM_DST + CH * 4;
constexpr int SM_SRC  = SM_TOTAL - CH * 4;
constexpr int SM_XL   = SM_XE;
constexpr int B_D = SM_BAR + 64, B_S = B_D + 24, B_X = B_S + 8;
constexpr int SM_W2   = SM_LB;
constexpr int SM_SAGG = SM_XE;
constexpr int SM_SQ   = SM_SAGG + NPB * 512;
static_assert(B_X + 8 <= SM_DST && SM_XR + NPB * 128 <= SM_W1B && SM_XL + XCAP * 8 <= SM_XR && SM_IND + 24576 == SM_XE + XE_P && SM_W1A + 20480 <= SM_RAW, "map");
static_assert(SM_XE + XE_P + 2 * XE_S <= SM_RAW && SM_SQ <= SM_QA && SM_SQ + NPB * 512 <= SM_TOTAL, "map");
static_assert(SM_STB + (G - 1) * RB + 2 * CH + 2 <= SM_SRC && SM_STA + (G - 1) * RA + 4 * CH + 4 <= SM_SRC, "run overflow is harmless");
static_assert(SM_TOTAL <= 232448, "smem");
static_assert(SM_W2 % 1024 == 0 && SM_QA % 1024 == 0 && SM_XO % 1024 == 0 && SM_W1A % 1024 == 0 && SM_W1B % 1024 == 0 &&
              SM_B1 % 16 == 0 && SM_TT % 16 == 0 && SM_BAR % 8 == 0 && SM_STA % 16 == 0 && SM_STB % 8 == 0 && SM_XR % 16 == 0 && SM_SRC % 16 == 0, "align");

__device__ uint4    g_ra[G * NCH * 16];
__device__ uint4    g_rb[G * NCH * 8];
__device__ uint32_t g_rx[G * NCH * 64];
__device__ uint4 g_xh[(NN + 1) * 8];
__device__ unsigned g_ctr;
#define TSTAMP(i, cond)
#define CSTAMP(i, cond)

__device__ __forceinline__ uint64_t mkdesc(uint32_t addr, uint32_t lbo, uint32_t sbo, uint32_t swz) {
    return (uint64_t)((addr & 0x3FFFF) >> 4) | ((uint64_t)(lbo >> 4) << 16) | ((uint64_t)(sbo >> 4) << 32) |
           ((uint64_t)swz << 62);
}
__device__ __forceinline__ void wg_fence()  { asm volatile("wgmma.fence.sync.aligned;" ::: "memory"); }
__device__ __forceinline__ void wg_commit() { asm volatile("wgmma.commit_group.sync.aligned;" ::: "memory"); }
template <int N> __device__ __forceinline__ void wg_wait() { asm volatile("wgmma.wait_group.sync.aligned %0;" ::"n"(N) : "memory"); }
__device__ __forceinline__ void fence_async() { asm volatile("fence.proxy.async.shared::cta;" ::: "memory"); }

#define R8(d, o) "+f"(d[o + 0]), "+f"(d[o + 1]), "+f"(d[o + 2]), "+f"(d[o + 3]), "+f"(d[o + 4]), "+f"(d[o + 5]), "+f"(d[o + 6]), "+f"(d[o + 7])
#define W8(d, o) "=f"(d[o + 0]), "=f"(d[o + 1]), "=f"(d[o + 2]), "=f"(d[o + 3]), "=f"(d[o + 4]), "=f"(d[o + 5]), "=f"(d[o + 6]), "=f"(d[o + 7])
#define U8(d, o) "+r"(d[o + 0]), "+r"(d[o + 1]), "+r"(d[o + 2]), "+r"(d[o + 3]), "+r"(d[o + 4]), "+r"(d[o + 5]), "+r"(d[o + 6]), "+r"(d[o + 7])
#define V8(d, o) "=r"(d[o + 0]), "=r"(d[o + 1]), "=r"(d[o + 2]), "=r"(d[o + 3]), "=r"(d[o + 4]), "=r"(d[o + 5]), "=r"(d[o + 6]), "=r"(d[o + 7])
#define L32 "{%0,%1,%2,%3,%4,%5,%6,%7,%8,%9,%10,%11,%12,%13,%14,%15,%16,%17,%18,%19,%20,%21,%22,%23,%24,%25,%26,%27,%28,%29,%30,%31}"
#define L48 "{%0,%1,%2,%3,%4,%5,%6,%7,%8,%9,%10,%11,%12,%13,%14,%15,%16,%17,%18,%19,%20,%21,%22,%23,%24,%25,%26,%27,%28,%29,%30,%31,%32,%33,%34,%35,%36,%37,%38,%39,%40,%41,%42,%43,%44,%45,%46,%47}"

__device__ __forceinline__ void h128z(uint32_t* d, const uint32_t* a, uint64_t db) {
    asm volatile("{.reg .pred p; setp.ne.b32 p, 0, 0;\n"
                 "wgmma.mma_async.sync.aligned.m64n128k16.f16.f16.f16 " L32 ", {%32,%33,%34,%35}, %36, p, 1, 1, 0;}"
                 : V8(d, 0), V8(d, 8), V8(d, 16), V8(d, 24) : "r"(a[0]), "r"(a[1]), "r"(a[2]), "r"(a[3]), "l"(db));
}
__device__ __forceinline__ void h128(uint32_t* d, const uint32_t* a, uint64_t db) {
    asm volatile("{.reg .pred p; setp.eq.b32 p, 0, 0;\n"
                 "wgmma.mma_async.sync.aligned.m64n128k16.f16.f16.f16 " L32 ", {%32,%33,%34,%35}, %36, p, 1, 1, 0;}"
                 : U8(d, 0), U8(d, 8), U8(d, 16), U8(d, 24) : "r"(a[0]), "r"(a[1]), "r"(a[2]), "r"(a[3]), "l"(db));
}
__device__ __forceinline__ void h128s(uint32_t* d, uint64_t da, uint64_t db) {
    asm volatile("{.reg .pred p; setp.eq.b32 p, 0, 0;\n"
                 "wgmma.mma_async.sync.aligned.m64n128k16.f16.f16.f16 " L32 ", %32, %33, p, 1, 1, 1, 0;}"
                 : U8(d, 0), U8(d, 8), U8(d, 16), U8(d, 24) : "l"(da), "l"(db));
}
__device__ __forceinline__ void r16t(float* d, const uint32_t* a, uint64_t db) {
    asm volatile("{.reg .pred p; setp.eq.b32 p, 0, 0;\n"
                 "wgmma.mma_async.sync.aligned.m64n16k16.f32.f16.f16 {%0,%1,%2,%3,%4,%5,%6,%7}, {%8,%9,%10,%11}, %12, p, 1, 1, 1;}"
                 : R8(d, 0) : "r"(a[0]), "r"(a[1]), "r"(a[2]), "r"(a[3]), "l"(db));
}
__device__ __forceinline__ void q_gemm(float* d, uint64_t da, uint64_t db) {
    asm volatile("{.reg .pred p, q; .reg .b64 a, b; setp.ne.b32 p, 0, 0; setp.eq.b32 q, 0, 0;\n"
                 "wgmma.fence.sync.aligned;\n"
                 "wgmma.mma_async.sync.aligned.m64n96k16.f32.bf16.bf16 " L48 ", %48, %49, p, 1, 1, 1, 0;\n"
                 "add.s64 a, %48, 128; add.s64 b, %49, 2;\n"
                 "wgmma.mma_async.sync.aligned.m64n96k16.f32.bf16.bf16 " L48 ", a, b, q, 1, 1, 1, 0;\n"
                 "add.s64 a, %48, 256; add.s64 b, %49, 4;\n"
                 "wgmma.mma_async.sync.aligned.m64n96k16.f32.bf16.bf16 " L48 ", a, b, q, 1, 1, 1, 0;\n"
                 "add.s64 a, %48, 384; add.s64 b, %49, 6;\n"
                 "wgmma.mma_async.sync.aligned.m64n96k16.f32.bf16.bf16 " L48 ", a, b, q, 1, 1, 1, 0;\n"
                 "wgmma.commit_group.sync.aligned;\n"
                 "wgmma.wait_group.sync.aligned 0;}"
                 : W8(d, 0), W8(d, 8), W8(d, 16), W8(d, 24), W8(d, 32), W8(d, 40)
                 : "l"(da), "l"(db) : "memory");
}
__device__ __forceinline__ void ss64t(float* d, uint64_t da, uint64_t db, int acc) {
    asm volatile("{.reg .pred p; setp.ne.b32 p, %34, 0;\n"
                 "wgmma.mma_async.sync.aligned.m64n64k16.f32.bf16.bf16 " L32 ", %32, %33, p, 1, 1, 0, 1;}"
                 : R8(d, 0), R8(d, 8), R8(d, 16), R8(d, 24)
                 : "l"(da), "l"(db), "r"(acc));
}
template <int NREG> __device__ __forceinline__ void fence_regs(float* d) {
#pragma unroll
    for (int i = 0; i < NREG; i++) asm volatile("" : "+f"(d[i])::"memory");
}
template <int NREG> __device__ __forceinline__ void fence_regs(uint32_t* d) {
#pragma unroll
    for (int i = 0; i < NREG; i++) asm volatile("" : "+r"(d[i])::"memory");
}
__device__ __forceinline__ void ldsm4t(uint32_t* r, uint32_t addr) {
    asm volatile("ldmatrix.sync.aligned.m8n8.x4.trans.shared.b16 {%0,%1,%2,%3}, [%4];"
                 : "=r"(r[0]), "=r"(r[1]), "=r"(r[2]), "=r"(r[3]) : "r"(addr) : "memory");
}
__device__ __forceinline__ void stsm4t(uint32_t addr, uint32_t a, uint32_t b, uint32_t c, uint32_t d) {
    asm volatile("stmatrix.sync.aligned.m8n8.x4.trans.shared.b16 [%0], {%1,%2,%3,%4};" ::"r"(addr), "r"(a), "r"(b), "r"(c), "r"(d) : "memory");
}
__device__ __forceinline__ void cp16(uint32_t s, const void* g) {
    asm volatile("cp.async.cg.shared.global [%0], [%1], 16;" ::"r"(s), "l"(g) : "memory");
}
__device__ __forceinline__ void cp4(uint32_t s, const void* g) {
    asm volatile("cp.async.ca.shared.global [%0], [%1], 4;" ::"r"(s), "l"(g) : "memory");
}
__device__ __forceinline__ void cp16z(uint32_t s, const void* g, uint32_t skip) {
    asm volatile("{.reg .pred p; setp.ne.u32 p, %2, 0; cp.async.cg.shared.global [%0], [%1], 16, p;}" ::"r"(s), "l"(g), "r"(skip) : "memory");
}
__device__ __forceinline__ void cp_commit() { asm volatile("cp.async.commit_group;" ::: "memory"); }
template <int N> __device__ __forceinline__ void cp_wait() { asm volatile("cp.async.wait_group %0;" ::"n"(N) : "memory"); }
__device__ __forceinline__ void cp_wait_all() { asm volatile("cp.async.wait_all;" ::: "memory"); }
__device__ __forceinline__ void mbar_init(uint32_t a, int cnt) { asm volatile("mbarrier.init.shared::cta.b64 [%0], %1;" ::"r"(a), "r"(cnt) : "memory"); }
__device__ __forceinline__ void bulk_load(uint32_t s, const void* g, uint32_t bytes, uint32_t bar) {
    asm volatile("mbarrier.arrive.expect_tx.shared::cta.b64 _, [%3], %2;\n"
                 "cp.async.bulk.shared::cluster.global.mbarrier::complete_tx::bytes [%0], [%1], %2, [%3];"
                 ::"r"(s), "l"(g), "r"(bytes), "r"(bar) : "memory");
}
__device__ __forceinline__ void mbar_arrive(uint32_t a) { asm volatile("mbarrier.arrive.shared::cta.b64 _, [%0];" ::"r"(a) : "memory"); }
__device__ __forceinline__ void mbar_cp_arrive(uint32_t a) { asm volatile("cp.async.mbarrier.arrive.noinc.shared::cta.b64 [%0];" ::"r"(a) : "memory"); }
__device__ __forceinline__ void mbar_wait(uint32_t a, uint32_t parity) {
    asm volatile("{.reg .pred p; .reg .u32 n; mov.u32 n, 0;\n"
                 "MW_%=: mbarrier.try_wait.parity.shared::cta.b64 p, [%0], %1;\n"
                 "@p bra MD_%=;\n"
                 "add.u32 n, n, 1; setp.gt.u32 p, n, 0x100000;\n"
                 "@p trap;\n"
                 "bra MW_%=;\n"
                 "MD_%=: }" ::"r"(a), "r"(parity) : "memory");
}
template <int ID, int CNT> __device__ __forceinline__ void bar_sync()   { asm volatile("bar.sync %0, %1;" ::"n"(ID), "n"(CNT) : "memory"); }
template <int ID, int CNT> __device__ __forceinline__ void bar_arrive() { asm volatile("bar.arrive %0, %1;" ::"n"(ID), "n"(CNT) : "memory"); }
template <int ID> __device__ __forceinline__ bool bar_or(bool v) {
    uint32_t r;
    asm volatile("{.reg .pred p, q; setp.ne.u32 q, %1, 0; bar.red.or.pred p, %2, 640, q; selp.u32 %0, 1, 0, p;}"
                 : "=r"(r) : "r"((uint32_t)v), "n"(ID) : "memory");
    return r != 0;
}
__device__ __forceinline__ float tanh_fast(float x) { float y; asm("tanh.approx.f32 %0, %1;" : "=f"(y) : "f"(x)); return y; }
__device__ __forceinline__ uint32_t pack2(float lo, float hi) {
    uint32_t r; asm("cvt.rn.bf16x2.f32 %0, %1, %2;" : "=r"(r) : "f"(hi), "f"(lo)); return r;
}
__device__ __forceinline__ uint32_t pack2h(float lo, float hi) {
    uint32_t r; asm("cvt.rn.f16x2.f32 %0, %1, %2;" : "=r"(r) : "f"(hi), "f"(lo)); return r;
}
__device__ __forceinline__ float bf_lo(uint32_t v) { return __uint_as_float(v << 16); }
__device__ __forceinline__ float bf_hi(uint32_t v) { return __uint_as_float(v & 0xFFFF0000u); }
__device__ __forceinline__ uint32_t bf2h(uint32_t v) { return pack2h(bf_lo(v), bf_hi(v)); }
__device__ __forceinline__ uint32_t amax2(uint32_t a, uint32_t b) {
    uint32_t r; asm("max.NaN.xorsign.abs.bf16x2 %0, %1, %2;" : "=r"(r) : "r"(a), "r"(b)); return r;
}
__device__ __forceinline__ uint32_t amax_fin(uint32_t m) { return max(m & 0x7FFFu, (m >> 16) & 0x7FFFu); }
__device__ __forceinline__ uint32_t silu_h2(uint32_t h) {
    uint32_t t, s;
    asm("tanh.approx.f16x2 %0, %1;" : "=r"(t) : "r"(h));
    asm("fma.rn.f16x2 %0, %1, %2, %1;" : "=r"(s) : "r"(h), "r"(t));
    return s;
}
__device__ __forceinline__ uint32_t hadd2(uint32_t a, uint32_t b) { uint32_t s; asm("add.rn.f16x2 %0, %1, %2;" : "=r"(s) : "r"(a), "r"(b)); return s; }
__device__ __forceinline__ uint32_t lds32(uint32_t a) { uint32_t v; asm volatile("ld.shared.b32 %0, [%1];" : "=r"(v) : "r"(a) : "memory"); return v; }
__device__ __forceinline__ uint32_t lds16(uint32_t a) { uint32_t v; asm volatile("ld.shared.u16 %0, [%1];" : "=r"(v) : "r"(a) : "memory"); return v; }
__device__ __forceinline__ uint4 lds128(uint32_t a) {
    uint4 v; asm volatile("ld.shared.v4.b32 {%0,%1,%2,%3}, [%4];" : "=r"(v.x), "=r"(v.y), "=r"(v.z), "=r"(v.w) : "r"(a) : "memory"); return v;
}
__device__ __forceinline__ void sts16(uint32_t a, uint32_t v) { asm volatile("st.shared.u16 [%0], %1;" ::"r"(a), "r"(v) : "memory"); }
__device__ __forceinline__ void sts32(uint32_t a, uint32_t v) { asm volatile("st.shared.b32 [%0], %1;" ::"r"(a), "r"(v) : "memory"); }
__device__ __forceinline__ void sts64(uint32_t a, uint32_t x, uint32_t y) { asm volatile("st.shared.v2.b32 [%0], {%1,%2};" ::"r"(a), "r"(x), "r"(y) : "memory"); }
__device__ __forceinline__ void sts128(uint32_t a, uint32_t x, uint32_t y, uint32_t z, uint32_t w) {
    asm volatile("st.shared.v4.b32 [%0], {%1,%2,%3,%4};" ::"r"(a), "r"(x), "r"(y), "r"(z), "r"(w) : "memory");
}
template <int V> __device__ __forceinline__ uint32_t atoms_add(uint32_t a) {
    uint32_t v; asm volatile("atom.shared.add.u32 %0, [%1], %2;" : "=r"(v) : "r"(a), "n"(V) : "memory"); return v;
}
__device__ __forceinline__ uint2 lds64(uint32_t a) {
    uint2 v; asm volatile("ld.shared.v2.b32 {%0,%1}, [%2];" : "=r"(v.x), "=r"(v.y) : "r"(a) : "memory"); return v;
}
__device__ __forceinline__ void st_rel32(uint32_t* p, uint32_t v) { asm volatile("st.relaxed.gpu.global.u32 [%0], %1;" ::"l"(p), "r"(v) : "memory"); }
__device__ __forceinline__ uint32_t ld_rel32(const void* p) {
    uint32_t v; asm volatile("ld.relaxed.gpu.global.u32 %0, [%1];" : "=r"(v) : "l"(p) : "memory"); return v;
}
__device__ __forceinline__ void st_rec(uint4* p, uint4 v) {
    uint64_t a = (uint64_t)v.x | ((uint64_t)v.y << 32), b = (uint64_t)v.z | ((uint64_t)v.w << 32);
    asm volatile("st.relaxed.gpu.global.v2.b64 [%0], {%1,%2};" ::"l"(p), "l"(a), "l"(b) : "memory");
}
__device__ __forceinline__ void st_rec1(uint2* p, uint2 v) {
    asm volatile("st.relaxed.gpu.global.b64 [%0], %1;" ::"l"(p), "l"((uint64_t)v.x | ((uint64_t)v.y << 32)) : "memory");
}
__device__ __forceinline__ uint4 ld_rec(const uint4* p) {
    uint64_t a, b;
    asm volatile("ld.relaxed.gpu.global.v2.b64 {%0,%1}, [%2];" : "=l"(a), "=l"(b) : "l"(p) : "memory");
    return make_uint4((uint32_t)a, (uint32_t)(a >> 32), (uint32_t)b, (uint32_t)(b >> 32));
}
__device__ __forceinline__ uint2 ld_rec1(const uint2* p) {
    uint64_t a;
    asm volatile("ld.relaxed.gpu.global.b64 %0, [%1];" : "=l"(a) : "l"(p) : "memory");
    return make_uint2((uint32_t)a, (uint32_t)(a >> 32));
}
__device__ __forceinline__ uint4 ld_stream(const void* p) {
    uint4 v;
    asm volatile("ld.global.nc.L1::no_allocate.v4.u32 {%0,%1,%2,%3}, [%4];" : "=r"(v.x), "=r"(v.y), "=r"(v.z), "=r"(v.w) : "l"(p));
    return v;
}
__device__ __forceinline__ void l2_prefetch(const void* p, uint32_t bytes) {
    asm volatile("cp.async.bulk.prefetch.L2.global [%0], %1;" ::"l"(p), "r"(bytes) : "memory");
}
__device__ __forceinline__ const char* madw(uint32_t a, uint32_t b, const char* p) {
    const char* r; asm("mad.wide.u32 %0, %1, %2, %3;" : "=l"(r) : "r"(a), "r"(b), "l"(p)); return r;
}
__device__ __forceinline__ uint64_t dsc(uint32_t lo, uint32_t hi) { return (uint64_t)lo | ((uint64_t)hi << 32); }
__device__ __forceinline__ uint32_t dlo(uint32_t addr) { return ((addr & 0x3FFFF) >> 4) | 0x10000u; }
constexpr uint32_t DH128 = (1024 >> 4) | (1u << 30), DH32A = (512 >> 4) | (3u << 30), DH32B = (256 >> 4) | (3u << 30);
__device__ __forceinline__ bool elect() {
    uint32_t r;
    asm volatile("{.reg .pred p; elect.sync _|p, 0xFFFFFFFF; selp.u32 %0, 1, 0, p;}" : "=r"(r));
    return r != 0;
}
__device__ __forceinline__ int node2row(int n) { return ((n >> 3) & 1) * 96 + (n >> 4) * 8 + (n & 7); }
__device__ __forceinline__ int row2node(int r) { return r < 96 ? (r >> 3) * 16 + (r & 7) : ((r - 96) >> 3) * 16 + 8 + (r & 7); }
__device__ __forceinline__ int col2pos(int c) { return (c & ~15) | ((c & 7) << 1) | ((c >> 3) & 1); }

struct Args {
    const __nv_bfloat16 *x, *ea;
    const int *src, *dst;
    const __nv_bfloat16 *w1, *b1, *w2, *b2;
    __nv_bfloat16* out;
};

__device__ __forceinline__ void rank4(uint32_t sb, const uint4& dv, uint32_t off, uint32_t* pa, uint32_t* w) {
    const uint32_t dd[4] = {dv.x, dv.y, dv.z, dv.w};
#pragma unroll
    for (int k = 0; k < 4; k++) {
        const uint32_t b = __umulhi(dd[k], 22605092u);
        pa[k] = atoms_add<4>(sb + SM_CNT + b * 4);
        w[k] = (dd[k] << 24) + (off + k) - b * ((uint32_t)NPB << 24);
    }
}
template <int PART> __device__ __forceinline__ void send_extra(uint32_t sb, int cta, int warp, int lane, uint32_t tg) {
    const bool all = (tg & (255u << 13)) == 0;
    const int rl = min(warp + 16 * lane, G);
    const uint32_t c = lds32(sb + SM_CNT + rl * 4);
    uint32_t m = __ballot_sync(0xFFFFFFFFu, rl < G && (all || c > sb + SM_STA + rl * RA + 256));
#pragma unroll 1
    while (m) {
        const int l = __ffs(m) - 1, r = warp + 16 * l;
        m &= m - 1;
        const uint32_t sa = sb + SM_STA + r * RA + 256 + lane * 4;
        if (sa < __shfl_sync(0xFFFFFFFFu, c, l) || all) {
            const uint32_t v = PART ? lds16(sb + SM_STB + r * RB + 128 + lane * 2) | (tg << 3) : (lds32(sa) & ~TAGM) | tg;
            st_rel32(g_rx + (r * NCH + cta) * 64 + PART * 32 + lane, v);
        }
    }
}
__device__ __forceinline__ void load_w2(uint32_t sb, int u, int nthr, const Args& a) {
    for (int i = u; i < 128 * 32; i += nthr) {
        const int kp = i >> 5, w = i & 31;
        const int k = (kp & ~15) | ((kp & 1) << 3) | ((kp >> 1) & 7);
        cp4(sb + SM_W2 + kp * 128 + (((w & 7) ^ (kp & 7)) << 4) + (w >> 3) * 4, a.w2 + k * 64 + w * 2);
    }
    if (u < 8) cp16(sb + SM_B2 + u * 16, a.b2 + u * 8);
    cp_wait_all();
}

__device__ __forceinline__ void tail_gemm(uint32_t sb, int wg, int warp4, int lane, int bucket, __nv_bfloat16* __restrict__ out) {
    const int g = lane >> 2, q = lane & 3;
    float d[32];
#pragma unroll
    for (int i = 0; i < 32; i++) d[i] = 0.f;
    wg_fence();
#pragma unroll
    for (int ks = 0; ks < 8; ks++)
        ss64t(d, mkdesc(sb + SM_QA + (ks >> 2) * 24576 + wg * 8192 + (ks & 3) * 32, 16, 1024, 1),
              mkdesc(sb + SM_W2 + ks * 2048, 16, 1024, 1), ks);
    wg_commit();
    const uint4 bb0 = lds128(sb + SM_B2 + q * 32), bb1 = lds128(sb + SM_B2 + q * 32 + 16);
    const int node0 = row2node(wg * 64 + warp4 * 16 + g);
    const uint32_t dg0 = lds32(sb + SM_DEG + node0 * 4) >> 2, dg1 = lds32(sb + SM_DEG + node0 * 4 + 64) >> 2;
    wg_wait<0>();
    fence_regs<32>(d);
    const uint32_t bw[8] = {bb0.x, bb0.y, bb0.z, bb0.w, bb1.x, bb1.y, bb1.z, bb1.w};
    uint32_t m = 0;
#pragma unroll
    for (int r = 0; r < 2; r++) {
        const int node = node0 + 16 * r;
        const int gn = bucket * NPB + node;
        const uint32_t dg = r ? dg1 : dg0;
        const float fd = (float)dg;
        uint32_t o[8];
#pragma unroll
        for (int j = 0; j < 8; j++) {
            const float v0 = fmaf(fd, bf_lo(bw[j]), d[4 * j + 2 * r]);
            const float v1 = fmaf(fd, bf_hi(bw[j]), d[4 * j + 2 * r + 1]);
            o[j] = dg ? pack2(v0, v1) : 0u;
            m = amax2(m, o[j]);
        }
        if (node < NPB && gn < NN) {
            uint4* op = reinterpret_cast<uint4*>(out + (size_t)gn * 64 + 16 * q);
            op[0] = make_uint4(o[0], o[1], o[2], o[3]);
            op[1] = make_uint4(o[4], o[5], o[6], o[7]);
        }
    }
    if (amax_fin(m) >= 0x7F80u) sts32(sb + F_NF, 1u);
}
__device__ __forceinline__ void tail_scan(uint32_t sb, int u) {
    uint32_t m = 0;
#pragma unroll
    for (int j = 0; j < 6; j++) {
        const int row = (u >> 3) + 32 * j;
        const uint32_t dg = lds32(sb + SM_DEG + row2node(row) * 4);
        const uint4 a = lds128(sb + SM_QA + row * 128 + (u & 7) * 16), b = lds128(sb + SM_QA + 24576 + row * 128 + (u & 7) * 16);
        const uint32_t v = amax2(amax2(amax2(a.x, a.y), amax2(a.z, a.w)), amax2(amax2(b.x, b.y), amax2(b.z, b.w)));
        if (dg) m = amax2(m, v);
    }
    const float thr = (float)lds32(sb + F_DMAX) * (1.f / 32768.f) * fmaf(88.f, bf_lo(lds32(sb + F_WMAX)), 30.f);
    if (bf_lo(amax_fin(m)) >= thr) sts32(sb + F_BIG, 1u);
}
__device__ __forceinline__ bool tail_failed(uint32_t sb) {
    bar_sync<1, NT>();
    return lds32(sb + F_NF) != 0 || lds32(sb + F_BIG) == 0;
}

__device__ __forceinline__ void slow_path(uint32_t sb, int bucket, const Args& a) {
    const int tid = threadIdx.x, lane = tid & 31, j = tid & 127, wg = tid >> 7;
    bar_sync<0, NT>();
    for (int i = tid; i < NPB * 128; i += NT) sts32(sb + SM_SAGG + i * 4, 0u);
    if (tid < 192) sts32(sb + SM_DEG + tid * 4, 0u);
    const unsigned short* w1u = reinterpret_cast<const unsigned short*>(a.w1);
    {
        uint32_t w[32];
#pragma unroll
        for (int k = 0; k < 32; k++) w[k] = w1u[(64 + 2 * k) * 128 + j] | ((uint32_t)w1u[(65 + 2 * k) * 128 + j] << 16);
        const float bj = __bfloat162float(a.b1[j]);
        for (int node = wg; node < NPB && bucket * NPB + node < NN; node += 5) {
            const uint4* xr = reinterpret_cast<const uint4*>(a.x + (size_t)(bucket * NPB + node) * 64);
            float h = bj;
            fence_regs<32>(w);
#pragma unroll
            for (int k = 0; k < 8; k++) {
                const uint4 v = __ldg(xr + k);
                const uint32_t vv[4] = {v.x, v.y, v.z, v.w};
#pragma unroll
                for (int i = 0; i < 4; i++) {
                    h = fmaf(bf_lo(vv[i]), bf_lo(w[4 * k + i]), h);
                    h = fmaf(bf_hi(vv[i]), bf_hi(w[4 * k + i]), h);
                }
            }
            sts32(sb + SM_SQ + (node * 128 + j) * 4, __float_as_uint(h));
        }
    }
    uint32_t w[40];
#pragma unroll
    for (int k = 0; k < 40; k++) {
        const int r = k < 32 ? 2 * k : 2 * k + 64;
        w[k] = w1u[r * 128 + j] | ((uint32_t)w1u[(r + 1) * 128 + j] << 16);
    }
    bar_sync<0, NT>();
    for (int e0 = wg * 32; e0 < NE; e0 += 160) {
        const int dn = a.dst[e0 + lane] - bucket * NPB;
        unsigned m = __ballot_sync(0xFFFFFFFFu, dn >= 0 && dn < NPB);
        while (m) {
            const int l = __ffs(m) - 1;
            m &= m - 1;
            const int node = __shfl_sync(0xFFFFFFFFu, dn, l);
            const int e = e0 + l;
            const uint4* xr = reinterpret_cast<const uint4*>(a.x + (size_t)a.src[e] * 64);
            const uint4* er = reinterpret_cast<const uint4*>(a.ea + (size_t)e * 16);
            float h = __uint_as_float(lds32(sb + SM_SQ + (node * 128 + j) * 4));
            fence_regs<40>(w);
#pragma unroll
            for (int k = 0; k < 10; k++) {
                const uint4 v = (k < 8) ? __ldg(xr + k) : __ldg(er + (k - 8));
                const uint32_t vv[4] = {v.x, v.y, v.z, v.w};
#pragma unroll
                for (int i = 0; i < 4; i++) {
                    h = fmaf(bf_lo(vv[i]), bf_lo(w[4 * k + i]), h);
                    h = fmaf(bf_hi(vv[i]), bf_hi(w[4 * k + i]), h);
                }
            }
            h *= 0.5f;
            const float f = fmaf(h, tanh_fast(h), h);
            asm volatile("red.shared.add.f32 [%0], %1;" ::"r"(sb + SM_SAGG + (node * 128 + j) * 4), "f"(f) : "memory");
            if (j == 0) atoms_add<4>(sb + SM_DEG + node * 4);
        }
    }
    bar_sync<0, NT>();
    load_w2(sb, tid, NT, a);
    for (int i = tid; i < NPB * 64; i += NT) {
        const int node = i >> 6, pr = i & 63;
        const int hid = (pr >> 3) * 16 + (pr & 7);
        const float u = __uint_as_float(lds32(sb + SM_SAGG + (node * 128 + hid) * 4));
        const float v = __uint_as_float(lds32(sb + SM_SAGG + (node * 128 + hid + 8) * 4));
        const int ch = (pr & 31) >> 2;
        sts32(sb + SM_QA + (pr >> 5) * 24576 + node2row(node) * 128 + ((ch ^ (node & 7)) << 4) + (pr & 3) * 4, pack2(u, v));
    }
    fence_async();
    bar_sync<0, NT>();
    if (wg < 3) tail_gemm(sb, wg, (tid >> 5) & 3, lane, bucket, a.out);
}

template <int MODE>
__device__ __forceinline__ bool producer(uint32_t sb, const Args& a) {
    const int tid = threadIdx.x, lane = tid & 31, warp = tid >> 5, warp4 = warp & 3, u = tid - 512;
    const int cta = blockIdx.x;
    const int e0 = cta * CH;
    const int nv = (MODE & 1) && cta < NCH ? min(CH, NE - e0) >> 2 : 0;
    const int nrow = min(NPB, NN - cta * NPB);
    if (u == 0) {
#pragma unroll
        for (int i = 0; i < 5; i++) mbar_init(sb + B_D + i * 8, 1);
        fence_async();
        if (nv) {
            bulk_load(sb + SM_DST, a.dst + e0, 8192, sb + B_D);
            bulk_load(sb + SM_DST + 8192, a.dst + e0 + 2048, 8192, sb + B_D + 8);
            bulk_load(sb + SM_DST + 16384, a.dst + e0 + 4096, nv * 16 - 16384, sb + B_D + 16);
            bulk_load(sb + SM_SRC, a.src + e0, nv * 16, sb + B_S);
        }
        bulk_load(sb + SM_XR, a.x + (size_t)cta * NPB * 64, nrow * 128, sb + B_X);
    }
    uint32_t ctr = 0;
    if (MODE == 3 && u == 96) ctr = ld_rel32(&g_ctr);
    if (u == 32) {
#pragma unroll
        for (int i = 0; i < 4; i++) {
            mbar_init(sb + SM_BAR + i * 8, 128 + 4);
            mbar_init(sb + SM_BAR + 32 + i * 8, 8);
        }
    }
    if (u == 64 && cta == G - 1) { l2_prefetch(a.w2, 16384); l2_prefetch(a.b2, 128); }
    bar_sync<9, NT>();
    if (MODE & 2) {
        if (nv) mbar_wait(sb + B_D + 16, 0);
        const int r = u >> 4, c = u & 15;
        const uint32_t sw = r * 128 + (((c & 7) ^ r) << 4);
        const __nv_bfloat16* wp = a.w1 + u * 8;
#pragma unroll
        for (int j = 0; j < 18; j++) {
            const uint32_t d = j < 8 ? SM_W1A + j * 1024 : j < 16 ? SM_W1B + (j - 8) * 1024 : SM_W1A + (j - 8) * 1024;
            cp16(sb + d + (c >> 3) * (j < 8 || j >= 16 ? 10240 : 8192) + sw, wp + j * 1024);
        }
        if (u < 16) cp16(sb + SM_B1 + u * 16, a.b1 + u * 8);
    }
    {
        const int xrow = u >> 3;
        uint4* hp = g_xh + (size_t)(cta * NPB + xrow) * 8 + (u & 7);
        const uint32_t xa = sb + SM_XO + xrow * 128 + (((u & 7) ^ (xrow & 7)) << 4);
        mbar_wait(sb + B_X, 0);
        CSTAMP(20, u == 0);
#pragma unroll
        for (int j = 0; j < 12; j++) {
            const int r = xrow + 16 * j;
            uint4 v = make_uint4(0u, 0u, 0u, 0u);
            if (r < nrow) v = lds128(sb + SM_XR + u * 16 + j * 2048);
            if ((MODE & 1) && r < NPB && r <= nrow) hp[j * 128] = make_uint4(bf2h(v.x), bf2h(v.y), bf2h(v.z), bf2h(v.w));
            if (MODE & 2) sts128(xa + j * 2048, v.x, v.y, v.z, v.w);
        }
    }
    if (!(MODE & 2)) return false;
    cp_wait_all();
    bar_sync<10, 128>();
    CSTAMP(16, u == 0);
    bool slow = false;
    int T = 0;
    if (warp == 19) {
        if (MODE == 3 && lane == 0) {
            asm volatile("fence.acq_rel.gpu;" ::: "memory");
            asm volatile("red.relaxed.gpu.global.inc.u32 [%0], %1;" ::"l"(&g_ctr), "r"(CTR_WRAP) : "memory");
            const uint32_t c0 = ctr / G * G;
            int it = 0;
            while (ld_rel32(&g_ctr) - c0 < (uint32_t)G)
                if (++it > (1 << 22)) __trap();
            asm volatile("fence.acq_rel.gpu;" ::: "memory");
        }
        __syncwarp();
        CSTAMP(13, lane == 0);
    } else {
        if (u < 80) {
            uint32_t m = 0;
#pragma unroll
            for (int c = 0; c < 16; c++) {
                const uint4 v = lds128(sb + SM_W1A + (c >> 3) * 10240 + u * 128 + (((c & 7) ^ (u & 7)) << 4));
                m = amax2(m, amax2(amax2(v.x, v.y), amax2(v.z, v.w)));
            }
            m = amax_fin(m);
            if (m != 0 && m < 0x3A00u) sts32(sb + F_BAD, 1u);
            asm volatile("red.shared.max.u32 [%0], %1;" ::"r"(sb + F_WMAX), "r"(m) : "memory");
        }
        __syncwarp();
        if (warp == 16) {
            bar_sync<3, 544>();
            uint32_t v[6], s = 0, dm = 0;
#pragma unroll
            for (int k = 0; k < 6; k++) {
                const uint32_t dg = lds32(sb + SM_DEG + (lane * 6 + k) * 4);
                v[k] = s;
                s += (dg + 4) & ~7u;
                dm = max(dm, dg);
            }
            uint32_t inc = s;
#pragma unroll
            for (int o = 1; o < 32; o <<= 1) {
                const uint32_t w = __shfl_up_sync(0xFFFFFFFFu, inc, o);
                if (lane >= o) inc += w;
            }
#pragma unroll
            for (int k = 0; k < 6; k++) sts32(sb + SM_BASE + (lane * 6 + k) * 4, sb + SM_LB + inc - s + v[k]);
            dm = __reduce_max_sync(0xFFFFFFFFu, dm);
            if (lane == 31) sts64(sb + F_TOT, inc >> 2, dm >> 2);
        }
        bar_sync<4, 608>();
        const int total = (int)lds32(sb + F_TOT);
        slow = lds32(sb + F_BAD) != 0 || total > CAP;
        if (!slow) {
            T = (total + 127) >> 7;
            const int T0 = (T + 1) >> 1;
#pragma unroll
            for (int k = 0; k < 2; k++) {
                const int n = u + 96 * k;
                const int dg = (int)lds32(sb + SM_DEG + n * 4) >> 2, b0 = (int)(lds32(sb + SM_BASE + n * 4) - sb - SM_LB) >> 2;
                const int b1 = b0 + ((dg + 1) & ~1);
                if (dg & 1) {
                    sts16(sb + SM_LA + (b0 + dg) * 2, NN);
                    sts32(sb + SM_LB + (b0 + dg) * 4, PADW);
                }
                const int w = min(n >> 3, 22);
                const uint32_t qlo = dlo(sb + SM_QA + ((w + 1) >> 1) * 1024), qhi = ((12288 - (w & 1) * 1024) >> 4) | (1u << 30);
                for (int t = (b0 + 127) >> 7; t * 128 < b1; t++) {
                    const uint32_t ta = sb + SM_TT + (t < T0 ? t : 32 + T - 1 - t) * 16;
                    sts32(ta + 4, qlo);
                    sts32(ta + 8, qhi);
                    if (t <= T0) sts32(sb + SM_TT + t * 16, n * 64);
                    if (t == T0) sts32(sb + SM_TT + (32 + T - T0) * 16, n * 64);
                }
                for (int t = max(b0 >> 7, T0); t * 128 + 127 < b1; t++) sts32(sb + SM_TT + (32 + T - 1 - t) * 16, n * 64);
                if (dg > 0 && b1 == total && T > 1) sts32(sb + SM_TT + 32 * 16, n * 64);
                if (dg > 0 && n >= 16 && lds32(sb + SM_BASE + ((n - 8) & ~7) * 4) > sb + SM_LB + (b0 & ~127) * 4) slow = true;
                const int p = total + n;
                if (p < T * 128) {
                    sts16(sb + SM_LA + p * 2, NN);
                    sts32(sb + SM_LB + p * 4, PADW);
                }
            }
            if (u == 0 && T == 1) sts32(sb + SM_TT + 16, NPB * 64);
        }
        CSTAMP(17, u == 0);
    }
    slow = bar_or<5>(slow);
    if (slow) return true;
    asm volatile("setmaxnreg.dec.sync.aligned.u32 64;");
    T = ((int)lds32(sb + F_TOT) + 127) >> 7;
    const int T0 = (T + 1) >> 1, T1 = T >> 1;

    const char* xb = reinterpret_cast<const char*>(g_xh) + (lane & 7) * 16;
    const char* eb = reinterpret_cast<const char*>(a.ea) + (lane & 1) * 16;
    const int ec = warp4 * 32 + (lane >> 1);
    const uint32_t elist = sb + SM_LB + col2pos(ec) * 4;
    const uint32_t raw = sb + SM_RAW + u * 16;
    auto fetch_e = [&](uint32_t ra, uint32_t l0, uint32_t l1) {
        cp16z(ra, madw(l0 & 0xFFFFFu, 32u, eb), l0 & PADW);
        cp16z(ra + 2048, madw(l1 & 0xFFFFFu, 32u, eb), l1 & PADW);
    };
#pragma unroll
    for (int i = 0; i < 4; i++) {
        const int t = (i & 1) ? T - 1 - (i >> 1) : i >> 1;
        if (i < T) fetch_e(raw + i * 4096, lds32(elist + t * 512), lds32(elist + t * 512 + 64));
        cp_commit();
    }
    const int xp0 = warp4 * 32 + (lane >> 3) * 8;
    uint32_t xoff[4];
#pragma unroll
    for (int i = 0; i < 4; i++) {
        const int c = (xp0 & ~15) + ((xp0 & 8) >> 1) + i;
        xoff[i] = sb + SM_XE + c * 128 + (((lane & 7) ^ (c & 7)) << 4);
    }
    const uint32_t eoff = sb + SM_XE + 16384 + ec * 32 + (((lane & 1) ^ ((ec >> 2) & 1)) << 4);
    const int oc = warp4 * 32 + lane;
    const uint32_t ilist = sb + SM_LB + col2pos(oc) * 4;
    const uint32_t ioff = sb + SM_IND + oc * 32 + (((oc >> 2) & 1) << 4);
    int i3 = 0;
    for (int k = 0; k < T0; k++) {
        if (k == 1) bar_sync<6, NT>();
#pragma unroll
        for (int s = 0; s < 2; s++) {
            if (s == 1 && k >= T1) break;
            const int t = s ? T - 1 - k : k, tn = s ? t - 2 : t + 2, st = 2 * s + (k & 1);
            const bool more = k + 2 < (s ? T1 : T0);
            const uint4 la = lds128(sb + SM_LA + t * 256 + xp0 * 2);
            const uint32_t own = lds32(ilist + t * 512);
            uint32_t l0, l1;
            if (more) { l0 = lds32(elist + tn * 512); l1 = lds32(elist + tn * 512 + 64); }
            const uint32_t ra = raw + (2 * (k & 1) + s) * 4096;
            cp_wait<3>();
            const uint4 e0 = lds128(ra), e1 = lds128(ra + 2048);
            const uint32_t ef[8] = {bf2h(e0.x), bf2h(e0.y), bf2h(e0.z), bf2h(e0.w), bf2h(e1.x), bf2h(e1.y), bf2h(e1.z), bf2h(e1.w)};
            const uint32_t ia = ioff + i3 + s * 4096;
            const uint32_t so = s * XE_S + (k & 1) * XE_P;
            mbar_wait(sb + SM_BAR + 32 + st * 8, ((k >> 1) & 1) ^ 1);
            const uint32_t lw[4] = {la.x, la.y, la.z, la.w};
#pragma unroll
            for (int i = 0; i < 4; i++) {
                cp16(xoff[i] + so, madw(lw[i] & 0xFFFFu, 128u, xb));
                cp16(xoff[i] + so + 1024, madw(lw[i] >> 16, 128u, xb));
            }
            mbar_cp_arrive(sb + SM_BAR + st * 8);
            sts128(eoff + so, ef[0], ef[1], ef[2], ef[3]);
            sts128(eoff + so + 512, ef[4], ef[5], ef[6], ef[7]);
            sts128(ia, 0u, 0u, 0u, 0u);
            sts128(ia ^ 16, 0u, 0u, 0u, 0u);
            if (!(own & PADW)) sts16(ia ^ ((own >> 23) & 30u), 0x3C00u);
            __syncwarp();
            if (lane == 0) mbar_arrive(sb + SM_BAR + st * 8);
            if (more) fetch_e(ra, l0, l1);
            cp_commit();
        }
        i3 = (i3 == 16384) ? 0 : i3 + 8192;
    }
    if (T0 < 2) bar_sync<6, NT>();
    bar_sync<10, 128>();
    load_w2(sb, u, 128, a);
    fence_async();
    bar_sync<1, NT>();
    tail_scan(sb, u + 128);
    if (!tail_failed(sb) || T == 0) return false;
    asm volatile("setmaxnreg.inc.sync.aligned.u32 96;");
    return true;
}

template <int MODE>
__device__ __forceinline__ bool consumer(uint32_t sb, const Args& a) {
    const int tid = threadIdx.x, lane = tid & 31, warp = tid >> 5, wg = tid >> 7, warp4 = warp & 3;
    const int cta = blockIdx.x;
    uint32_t tg = 1u << 13;
    const uint4* ga = g_ra + (size_t)(cta * NCH + warp * 8) * 16 + lane;
    uint4 rv[4];
    {
        const int e0 = cta * CH;
        const int nv = (MODE & 1) && cta < NCH ? min(CH, NE - e0) >> 2 : 0;
        uint32_t ctr = 0;
        if (MODE == 3 && tid == 0) ctr = ld_rel32(&g_ctr);
        if (tid < 200) sts32(sb + SM_DEG + tid * 4, 0u);
        else if (tid >= 256 && tid <= 256 + G) sts32(sb + SM_CNT + (tid - 256) * 4, sb + SM_STA + (tid - 256) * RA + 4);
        bar_sync<9, NT>();
        uint32_t pa[16];
#pragma unroll
        for (int j = 0; j < 4; j++)
            if (tid + 512 * j < nv) {
                uint32_t w[4];
                if (j < 3) mbar_wait(sb + B_D + j * 8, 0);
                if (j == 0) CSTAMP(2, tid == 0);
                rank4(sb, lds128(sb + SM_DST + tid * 16 + j * 8192), (tid + 512 * j) * 4, pa + 4 * j, w);
#pragma unroll
                for (int k = 0; k < 4; k++) sts32(pa[4 * j + k], w[k]);
            }
        if (MODE == 3 && tid == 0) sts32(sb + F_TAG, ((ctr / G + 1) & 511u) << 13);
        CSTAMP(3, tid == 0);
        bar_sync<2, 512>();
        if (MODE == 3) tg = lds32(sb + F_TAG);
        bool extra = false;
        if (nv) {
            bool bad = false;
#pragma unroll
            for (int i = 0; i < 5; i++) {
                const int r = min(lane + 32 * i, G);
                const uint32_t c = lds32(sb + SM_CNT + r * 4) - r * RA;
                bad |= c > sb + SM_STA + 384;
                extra |= c > sb + SM_STA + 256;
            }
            bad = __any_sync(0xFFFFFFFFu, bad);
            extra = __any_sync(0xFFFFFFFFu, extra && (lane & 15) == warp) || (tg & (255u << 13)) == 0;
            const int r0 = 2 * warp + (lane >> 4);
            uint4* gp = g_ra + (size_t)(r0 * NCH + cta) * 16 + (lane & 15);
#pragma unroll
            for (int j = 0; j < 5; j++)
                if (j < 4 || warp < 2) {
                    uint4 v = lds128(sb + SM_STA + (r0 + 32 * j) * RA + (lane & 15) * 16);
                    const uint32_t c = lds32(sb + SM_CNT + (r0 + 32 * j) * 4);
                    if ((lane & 15) == 0) v.x = bad ? BADH : c;
                    v.y = (v.y & ~TAGM) | tg;
                    v.w = (v.w & ~TAGM) | tg;
                    st_rec(gp + j * 32 * NCH * 16, v);
                }
            if (extra) send_extra<0>(sb, cta, warp, lane, tg);
        }
        CSTAMP(4, tid == 0);
        const uint32_t cb = sb + SM_STB - ((sb + SM_STA) >> 1);
        if (nv) mbar_wait(sb + B_S, 0);
        CSTAMP(21, tid == 0);
#pragma unroll
        for (int j = 0; j < 4; j++)
            if (tid + 512 * j < nv) {
                const uint4 sv = lds128(sb + SM_SRC + tid * 16 + j * 8192);
                sts16((pa[4 * j] >> 1) + cb, sv.x);
                sts16((pa[4 * j + 1] >> 1) + cb, sv.y);
                sts16((pa[4 * j + 2] >> 1) + cb, sv.z);
                sts16((pa[4 * j + 3] >> 1) + cb, sv.w);
            }
        bar_sync<2, 512>();
        CSTAMP(5, tid == 0);
        if (MODE & 2) {
#pragma unroll
            for (int j = 0; j < 4; j++) rv[j] = ld_rec(ga + j * 32);
        }
        if (nv) {
            const int r0 = 2 * warp + (lane >> 4);
            uint2* gp = reinterpret_cast<uint2*>(g_rb) + (size_t)(r0 * NCH + cta) * 16 + (lane & 15);
            const uint32_t par = (tg << 2) & 0x8000u;
#pragma unroll
            for (int j = 0; j < 5; j++)
                if (j < 4 || warp < 2) {
                    uint2 v = lds64(sb + SM_STB + (r0 + 32 * j) * RB + (lane & 15) * 8);
                    v.x = (v.x & ~0x8000u) | par;
                    st_rec1(gp + j * 32 * NCH * 16, v);
                }
            if (extra) send_extra<1>(sb, cta, warp, lane, tg);
        }
    }
    if (!(MODE & 2)) return false;
    CSTAMP(6, tid == 0);

    int rem[4];
    uint32_t rk[16];
    bool extra = false;
#pragma unroll
    for (int j = 0; j < 4; j++) {
        if (MODE == 3) {
            int it = 0;
            while (((rv[j].y ^ tg) | (rv[j].w ^ tg)) & TAGM) {
                if (++it > (1 << 22)) __trap();
                rv[j] = ld_rec(ga + j * 32);
            }
        }
        const uint32_t n4 = __shfl_sync(0xFFFFFFFFu, rv[j].x, lane & 16) - (sb + SM_STA + cta * RA);
        rem[j] = (int)n4 - (lane & 15) * 16;
        if (n4 > 384u) { sts32(sb + F_BAD, 1u); rem[j] = 0; }
        extra |= n4 > 256u;
        if (rem[j] > 0 && (lane & 15)) rk[4 * j] = atoms_add<4>(sb + SM_DEG + (rv[j].x >> 22));
        if (rem[j] > 4) rk[4 * j + 1] = atoms_add<4>(sb + SM_DEG + (rv[j].y >> 22));
        if (rem[j] > 8) rk[4 * j + 2] = atoms_add<4>(sb + SM_DEG + (rv[j].z >> 22));
        if (rem[j] > 12) rk[4 * j + 3] = atoms_add<4>(sb + SM_DEG + (rv[j].w >> 22));
    }
    const uint2* gb = reinterpret_cast<const uint2*>(g_rb) + (size_t)(cta * NCH + warp * 8) * 16 + lane;
    uint2 rb[4];
#pragma unroll
    for (int j = 0; j < 4; j++) rb[j] = ld_rec1(gb + j * 32);
    if (__any_sync(0xFFFFFFFFu, extra)) {
        int nn = 0;
#pragma unroll
        for (int j = 0; j < 4; j++) {
            const int v = __shfl_sync(0xFFFFFFFFu, rem[j], (lane & 1) * 16);
            if ((lane >> 1) == j) nn = v;
        }
        uint32_t m = __ballot_sync(0xFFFFFFFFu, nn > 256);
#pragma unroll 1
        while (m) {
            const int l = __ffs(m) - 1, r = warp * 8 + l;
            m &= m - 1;
            if (256 + lane * 4 < __shfl_sync(0xFFFFFFFFu, nn, l)) {
                uint32_t w = ld_rel32(g_rx + (cta * NCH + r) * 64 + lane);
                if (MODE == 3) {
                    int it = 0;
                    while ((w ^ tg) & TAGM) {
                        if (++it > (1 << 22)) __trap();
                        w = ld_rel32(g_rx + (cta * NCH + r) * 64 + lane);
                    }
                }
                const uint32_t q = atoms_add<4>(sb + SM_DEG + (w >> 22)), ix = atoms_add<1>(sb + F_XC);
                if (ix < XCAP) sts64(sb + SM_XL + ix * 8, w - tg + r * CH, (q & 0xFFFFu) | ((r * 64 + 32 + lane) << 16));
                else sts32(sb + F_BAD, 1u);
            }
        }
    }
    __syncwarp();
    CSTAMP(7, tid == 0);
    bar_arrive<3, 544>();
    bar_sync<4, 608>();
    CSTAMP(8, tid == 0);
    const int total = (int)lds32(sb + F_TOT);
    bool slow = lds32(sb + F_BAD) != 0 || total > CAP;
    const int T = (total + 127) >> 7;
    if (!slow) {
        const uint32_t cl = sb + SM_LA - ((sb + SM_LB) >> 1);
        const uint32_t xc = lds32(sb + F_XC);
#pragma unroll
        for (int j = 0; j < 4; j++) {
            if (rem[j] > 0 && (lane & 15)) rk[4 * j] += lds32(sb + SM_BASE + (rv[j].x >> 22));
            if (rem[j] > 4) rk[4 * j + 1] += lds32(sb + SM_BASE + (rv[j].y >> 22));
            if (rem[j] > 8) rk[4 * j + 2] += lds32(sb + SM_BASE + (rv[j].z >> 22));
            if (rem[j] > 12) rk[4 * j + 3] += lds32(sb + SM_BASE + (rv[j].w >> 22));
        }
#pragma unroll
        for (int j = 0; j < 4; j++) {
            const uint32_t c0 = (warp * 8 + 2 * j + (lane >> 4)) * CH, c1 = c0 - tg;
            if (rem[j] > 0 && (lane & 15)) sts32(rk[4 * j], rv[j].x + c0);
            if (rem[j] > 4) sts32(rk[4 * j + 1], rv[j].y + c1);
            if (rem[j] > 8) sts32(rk[4 * j + 2], rv[j].z + c0);
            if (rem[j] > 12) sts32(rk[4 * j + 3], rv[j].w + c1);
        }
#pragma unroll
        for (int j = 0; j < 4; j++) {
            if (MODE == 3) {
                int it = 0;
                while ((rb[j].x ^ (tg << 2)) & 0x8000u) {
                    if (++it > (1 << 22)) __trap();
                    rb[j] = ld_rec1(gb + j * 32);
                }
            }
            if (rem[j] > 0 && (lane & 15)) sts16((rk[4 * j] >> 1) + cl, rb[j].x & 0x7FFFu);
            if (rem[j] > 4) sts16((rk[4 * j + 1] >> 1) + cl, rb[j].x >> 16);
            if (rem[j] > 8) sts16((rk[4 * j + 2] >> 1) + cl, rb[j].y);
            if (rem[j] > 12) sts16((rk[4 * j + 3] >> 1) + cl, rb[j].y >> 16);
        }
        if (tid < xc) {
            const uint2 e = lds64(sb + SM_XL + tid * 8);
            const uint32_t p = lds32(sb + SM_BASE + (e.x >> 22)) + (e.y & 0xFFFFu);
            const uint32_t* gx = g_rx + cta * NCH * 64 + (e.y >> 16);
            uint32_t w = ld_rel32(gx);
            if (MODE == 3) {
                int it = 0;
                while ((w >> 16) != (tg >> 13)) {
                    if (++it > (1 << 22)) __trap();
                    w = ld_rel32(gx);
                }
            }
            sts32(p, e.x);
            sts16((p >> 1) + cl, w);
        }
    }
    __syncwarp();
    CSTAMP(18, tid == 0);
    slow = bar_or<5>(slow);
    if (slow) return true;
    asm volatile("setmaxnreg.inc.sync.aligned.u32 104;");
    CSTAMP(14, tid == 0);
    const int s = wg >> 1, h = wg & 1;
    fence_async();
    {
        float d[48];
        const float ba = 0.5f * bf_lo(lds16(sb + SM_B1 + (h * 64 + warp4 * 16 + (lane >> 2)) * 2));
        const float bb = 0.5f * bf_lo(lds16(sb + SM_B1 + (h * 64 + warp4 * 16 + (lane >> 2)) * 2 + 16));
        q_gemm(d, mkdesc(sb + SM_W1B + h * 8192, 16, 1024, 1), mkdesc(sb + SM_XO + s * 12288, 16, 1024, 1));
        const uint32_t qa = sb + SM_QA + h * 24576 + (lane >> 4) * 12288 + s * 6144 + (lane & 7) * 128 +
                            (((2 * warp4 + ((lane >> 3) & 1)) ^ (lane & 7)) << 4);
#pragma unroll
        for (int j = 0; j < 6; j++) {
            const float* e = d + 8 * j;
            stsm4t(qa + j * 1024, pack2h(fmaf(e[0], 0.5f, ba), fmaf(e[1], 0.5f, ba)), pack2h(fmaf(e[2], 0.5f, bb), fmaf(e[3], 0.5f, bb)),
                   pack2h(fmaf(e[4], 0.5f, ba), fmaf(e[5], 0.5f, ba)), pack2h(fmaf(e[6], 0.5f, bb), fmaf(e[7], 0.5f, bb)));
        }
    }
    uint32_t w1f[5][4];
    {
        const int kr = (lane & 7) + 8 * (lane >> 4), ch = 2 * warp4 + ((lane >> 3) & 1);
#pragma unroll
        for (int ks = 0; ks < 5; ks++) {
            ldsm4t(w1f[ks], sb + SM_W1A + h * 10240 + (16 * ks + kr) * 128 + ((ch ^ (kr & 7)) << 4));
#pragma unroll
            for (int i = 0; i < 4; i++) w1f[ks][i] = pack2h(0.5f * bf_lo(w1f[ks][i]), 0.5f * bf_hi(w1f[ks][i]));
        }
    }
    fence_async();
    __syncwarp();
    bar_arrive<6, NT>();
    if (h) bar_sync<8, 256>(); else bar_sync<7, 256>();
    CSTAMP(19, tid == 0);

    {
        const int wgu = __shfl_sync(0xFFFFFFFFu, wg, 0), Tu = __shfl_sync(0xFFFFFFFFu, T, 0);
        const int su = wgu >> 1, hu = wgu & 1;
        const int Ts = su ? Tu >> 1 : (Tu + 1) >> 1;
        if (Ts > 0) {
            const int q = lane & 3;
            const uint32_t a0 = q * 256 + (((2 * warp4 + (lane >> 4)) ^ (2 * q)) << 4) + ((lane >> 2) & 3) * 4, a1 = (a0 + 128) ^ 16;
            const uint32_t c0 = sb + SM_QA + hu * 24576 + (su ? 0 : 960) - 128 * q;
            uint32_t acc[32], pk[16], fa[4];
            float agg[8];
#pragma unroll
            for (int i = 0; i < 8; i++) agg[i] = 0.f;
#pragma unroll
            for (int i = 0; i < 16; i++) pk[i] = 0u;
            auto flush = [&](uint32_t F, bool on) {
                const uint32_t v = F + c0;
#pragma unroll
                for (int j = 0; j < 4; j++) {
                    const int i0 = (j >> 1) * 4 + (j & 1);
                    const uint32_t t = v - 64 * (j & 1) - 512 * (j >> 1);
                    if (on && ((t ^ fa[j]) & ~1023u)) {
                        sts32(fa[j] + (j >> 1) * 12288, pack2(agg[i0], agg[i0 + 2]));
                        agg[i0] = 0.f;
                        agg[i0 + 2] = 0.f;
                    }
                    asm("lop3.b32 %0, %1, %0, 1023, 0xD8;" : "+r"(fa[j]) : "r"(t));
                }
            };
            fa[0] = fa[2] = a0;
            fa[1] = fa[3] = a1;
            const uint32_t tta = sb + SM_TT + su * 512;
            uint4 tt = lds128(tta);
            flush(tt.x, false);
            const uint32_t ifirst = dlo(sb + SM_IND + su * 4096), ilast = ifirst + 1024;
            uint32_t iprev = ifirst, icur = ifirst;
            const uint32_t x0 = dlo(sb + SM_XE + su * XE_S), bar0 = sb + SM_BAR + 2 * su * 8;
            for (int k = 0; k < Ts; k++) {
                const uint32_t dx = x0 + (k & 1) * (XE_P >> 4), bar = bar0 + (k & 1) * 8;
                mbar_wait(bar, (k >> 1) & 1);
                fence_async();
                wg_fence();
#pragma unroll
                for (int kk = 0; kk < 4; kk++) r16t(agg, pk + 4 * kk, dsc(iprev + kk * 64, DH32A));
                wg_commit();
                h128z(acc, w1f[0], dsc(dx, DH128));
                h128(acc, w1f[1], dsc(dx + 2, DH128));
                h128(acc, w1f[2], dsc(dx + 4, DH128));
                h128(acc, w1f[3], dsc(dx + 6, DH128));
                h128(acc, w1f[4], dsc(dx + 1024, DH32B));
                h128s(acc, dsc(tt.y + hu * 1536, tt.z), dsc(icur, DH32B));
                wg_commit();
                wg_wait<1>();
                fence_regs<8>(agg);
                fence_regs<16>(pk);
                flush(tt.x, true);
                tt = lds128(tta + (k + 1) * 16);
                wg_wait<0>();
                fence_regs<32>(acc);
                if (elect()) mbar_arrive(bar + 32);
#pragma unroll
                for (int i = 0; i < 16; i++) {
                    const int i0 = (i >> 1) * 4 + (i & 1);
                    pk[i] = hadd2(silu_h2(acc[i0]), silu_h2(acc[i0 + 2]));
                }
                fence_regs<16>(pk);
                iprev = icur;
                icur = icur == ilast ? ifirst : icur + 512;
            }
            wg_fence();
#pragma unroll
            for (int kk = 0; kk < 4; kk++) r16t(agg, pk + 4 * kk, dsc(iprev + kk * 64, DH32A));
            wg_commit();
            wg_wait<0>();
            fence_regs<8>(agg);
            flush(tt.x, true);
            if (Tu > 1) {
                const int sl = (tt.x >> 6) & 15;
                const bool mine = q == ((sl & 7) >> 1);
                const uint32_t xa = sb + SM_XB + hu * 256 + (warp4 * 8 + (lane >> 2)) * 8;
                const float v0 = (sl & 8) ? ((sl & 1) ? agg[5] : agg[4]) : ((sl & 1) ? agg[1] : agg[0]);
                const float v1 = (sl & 8) ? ((sl & 1) ? agg[7] : agg[6]) : ((sl & 1) ? agg[3] : agg[2]);
                if (su) {
                    if (mine) sts64(xa, __float_as_uint(v0), __float_as_uint(v1));
                    if (hu) bar_arrive<8, 256>(); else bar_arrive<7, 256>();
                } else {
                    if (hu) bar_sync<8, 256>(); else bar_sync<7, 256>();
                    const uint32_t ra = (sl & 8) ? ((sl & 1) ? fa[3] : fa[2]) + 12288 : ((sl & 1) ? fa[1] : fa[0]);
                    if (mine) sts32(ra, pack2(v0 + __uint_as_float(lds32(xa)), v1 + __uint_as_float(lds32(xa + 4))));
                }
            }
        }
    }
    CSTAMP(10, tid == 0);
    fence_async();
    bar_sync<1, NT>();
    if (wg < 3) tail_gemm(sb, wg, warp4, lane, cta, a.out);
    else tail_scan(sb, tid - 384);
    CSTAMP(15, tid == 0);
    if (!tail_failed(sb) || T == 0) return false;
    asm volatile("setmaxnreg.dec.sync.aligned.u32 96;");
    return true;
}

template <int MODE>
__global__ void __launch_bounds__(NT, 1) mpnn_kernel(const __grid_constant__ Args a) {
    extern __shared__ __align__(1024) uint8_t smem[];
    const uint32_t sb = (uint32_t)__cvta_generic_to_shared(smem);
    TSTAMP(0, threadIdx.x == 0);
    CSTAMP(1, threadIdx.x == 0);
    const bool slow = threadIdx.x >= 512 ? producer<MODE>(sb, a) : consumer<MODE>(sb, a);
    if ((MODE & 2) && slow) slow_path(sb, blockIdx.x, a);
    CSTAMP(11, threadIdx.x == 0);
    TSTAMP(12, threadIdx.x == 0);
}

}

extern "C" void kernel_launch(void* const* d_in, const int* in_sizes, int n_in, void* d_out, int out_size) {
    (void)in_sizes; (void)n_in; (void)out_size;
    static int fused = -1;
    if (fused < 0) {
        int dev = 0, sms = 0, nb = 0;
        cudaGetDevice(&dev);
        cudaDeviceGetAttribute(&sms, cudaDevAttrMultiProcessorCount, dev);
        cudaFuncSetAttribute(mpnn_kernel<1>, cudaFuncAttributeMaxDynamicSharedMemorySize, SM_TOTAL);
        cudaFuncSetAttribute(mpnn_kernel<2>, cudaFuncAttributeMaxDynamicSharedMemorySize, SM_TOTAL);
        cudaFuncSetAttribute(mpnn_kernel<3>, cudaFuncAttributeMaxDynamicSharedMemorySize, SM_TOTAL);
        cudaOccupancyMaxActiveBlocksPerMultiprocessor(&nb, mpnn_kernel<3>, NT, SM_TOTAL);
        fused = (sms * nb >= G) ? 1 : 0;
    }
    Args a;
    a.x   = (const __nv_bfloat16*)d_in[0];
    a.ea  = (const __nv_bfloat16*)d_in[1];
    a.src = (const int*)d_in[2];
    a.dst = (const int*)d_in[3];
    a.w1  = (const __nv_bfloat16*)d_in[4];
    a.b1  = (const __nv_bfloat16*)d_in[5];
    a.w2  = (const __nv_bfloat16*)d_in[6];
    a.b2  = (const __nv_bfloat16*)d_in[7];
    a.out = (__nv_bfloat16*)d_out;
    cudaStream_t s = cudaStreamPerThread;
    if (fused) {
        mpnn_kernel<3><<<G, NT, SM_TOTAL, s>>>(a);
    } else {
        mpnn_kernel<1><<<G, NT, SM_TOTAL, s>>>(a);
        mpnn_kernel<2><<<G, NT, SM_TOTAL, s>>>(a);
    }
}
```

```cpp
#include <cuda_runtime.h>
#include <cuda_bf16.h>
#include <stdint.h>

#define XAT 0
#define W1AT 1
namespace {

constexpr int NN   = 25000;
constexpr int NE   = 800000;
constexpr int G    = 132;
constexpr int NPB  = 190;
constexpr int CH   = 6064;
constexpr int CAPT = 52;
constexpr int CAP  = CAPT * 128;
constexpr int NT   = 640;
constexpr int CAPB = 48;
constexpr int OVC  = 64;
constexpr int BINP = CAPB * 4 + 4;
constexpr int RP   = 304;
constexpr int RS   = RP / 4 - 1, RU = RP / 16, RX = 32;
constexpr uint32_t CINC = (1u << 18) + 4u;
constexpr uint32_t RUNL = (uint32_t)RS << 18, BINL = (uint32_t)(CAPB + 1) << 18;
constexpr uint32_t TAGM = 511u << 13, PADW = 0x800000u;

constexpr int SM_CNT  = 0;
constexpr int SM_DEG  = 576;
constexpr int SM_FLAG = SM_DEG + 896;
constexpr int SM_TT   = SM_FLAG + 32;
constexpr int SM_XB   = SM_TT + 1024;
constexpr int SM_B1   = SM_XB + 512;
constexpr int SM_B2   = SM_B1 + 256;
constexpr int SM_BAR  = SM_B2 + 128;
constexpr int SM_XE   = 5120;
constexpr int XE_S    = 20480, XE_P = 65536;
constexpr int SM_IND  = SM_XE + 2 * XE_S;
constexpr int SM_POS  = SM_XE + XE_P + 2 * XE_S;
constexpr int SM_RAW  = 126976;
constexpr int SM_QA   = SM_RAW + 16384;
constexpr int SM_BIN  = SM_QA + 49152;
constexpr int SM_OVL  = SM_BIN + NPB * BINP;
constexpr int SM_SR   = SM_OVL + OVC * 8 + 8;
constexpr int SM_TOTAL = SM_SR + 2048;
constexpr uint32_t OVLO = SM_OVL - SM_BIN, PADO = OVLO + OVC * 8;
constexpr int F_TOT = SM_FLAG, F_DMAX = SM_FLAG + 4, F_BAD = SM_FLAG + 8, F_WMAX = SM_FLAG + 12, F_NF = SM_FLAG + 16,
              F_BIG = SM_FLAG + 20, F_XC = SM_FLAG + 28;
constexpr int SM_XR   = SM_XE;
constexpr int SM_W1B  = SM_XR + 24576;
constexpr int SM_XO   = SM_W1B + 16384;
constexpr int SM_W1A  = SM_XO + 24576;
constexpr int SM_STA  = SM_W1A + 20480;
constexpr int B_X = SM_BAR + 64;
constexpr int SM_W2   = SM_BIN;
constexpr int SM_SAGG = SM_XE;
constexpr int SM_SQ   = SM_SAGG + NPB * 512;
static_assert(B_X + 8 <= SM_XE && SM_IND + 24576 == SM_XE + XE_P && SM_POS + CAP * 2 <= SM_RAW && SM_STA + G * RP <= SM_QA, "map");
static_assert(SM_SQ <= SM_QA && SM_SQ + NPB * 512 <= SM_TOTAL && SM_TOTAL <= 232448 && PADO < 65536, "map");
static_assert(G * (RS + RX) + 2 < 16384 && G * RU <= 5 * 512 && G * CH >= NE && NE - (G - 1) * CH > 4096 && CH <= 6144 && CH % 4 == 0, "fields");
static_assert(SM_W2 % 1024 == 0 && SM_QA % 1024 == 0 && SM_XO % 1024 == 0 && SM_W1A % 1024 == 0 && SM_W1B % 1024 == 0 &&
              SM_B1 % 16 == 0 && SM_TT % 16 == 0 && SM_BAR % 8 == 0 && SM_STA % 16 == 0 && SM_OVL % 8 == 0 && SM_XR % 16 == 0 && SM_SR % 16 == 0 && SM_DEG % 16 == 0, "align");

__device__ uint4 g_ra[G * G * RU];
__device__ uint2 g_rx[G * G * RX];
__device__ uint4 g_xh[(NN + 1) * 8];
__device__ uint32_t g_ctl[(G + 1) * 32];
#define TSTAMP(i, cond)
#define CSTAMP(i, cond)

__device__ __forceinline__ uint64_t mkdesc(uint32_t addr, uint32_t lbo, uint32_t sbo, uint32_t swz) {
    return (uint64_t)((addr & 0x3FFFF) >> 4) | ((uint64_t)(lbo >> 4) << 16) | ((uint64_t)(sbo >> 4) << 32) |
           ((uint64_t)swz << 62);
}
__device__ __forceinline__ void wg_fence()  { asm volatile("wgmma.fence.sync.aligned;" ::: "memory"); }
__device__ __forceinline__ void wg_commit() { asm volatile("wgmma.commit_group.sync.aligned;" ::: "memory"); }
template <int N> __device__ __forceinline__ void wg_wait() { asm volatile("wgmma.wait_group.sync.aligned %0;" ::"n"(N) : "memory"); }
__device__ __forceinline__ void fence_async() { asm volatile("fence.proxy.async.shared::cta;" ::: "memory"); }

#define R8(d, o) "+f"(d[o + 0]), "+f"(d[o + 1]), "+f"(d[o + 2]), "+f"(d[o + 3]), "+f"(d[o + 4]), "+f"(d[o + 5]), "+f"(d[o + 6]), "+f"(d[o + 7])
#define W8(d, o) "=f"(d[o + 0]), "=f"(d[o + 1]), "=f"(d[o + 2]), "=f"(d[o + 3]), "=f"(d[o + 4]), "=f"(d[o + 5]), "=f"(d[o + 6]), "=f"(d[o + 7])
#define U8(d, o) "+r"(d[o + 0]), "+r"(d[o + 1]), "+r"(d[o + 2]), "+r"(d[o + 3]), "+r"(d[o + 4]), "+r"(d[o + 5]), "+r"(d[o + 6]), "+r"(d[o + 7])
#define V8(d, o) "=r"(d[o + 0]), "=r"(d[o + 1]), "=r"(d[o + 2]), "=r"(d[o + 3]), "=r"(d[o + 4]), "=r"(d[o + 5]), "=r"(d[o + 6]), "=r"(d[o + 7])
#define L32 "{%0,%1,%2,%3,%4,%5,%6,%7,%8,%9,%10,%11,%12,%13,%14,%15,%16,%17,%18,%19,%20,%21,%22,%23,%24,%25,%26,%27,%28,%29,%30,%31}"
#define L48 "{%0,%1,%2,%3,%4,%5,%6,%7,%8,%9,%10,%11,%12,%13,%14,%15,%16,%17,%18,%19,%20,%21,%22,%23,%24,%25,%26,%27,%28,%29,%30,%31,%32,%33,%34,%35,%36,%37,%38,%39,%40,%41,%42,%43,%44,%45,%46,%47}"

__device__ __forceinline__ void h128z(uint32_t* d, const uint32_t* a, uint64_t db) {
    asm volatile("{.reg .pred p; setp.ne.b32 p, 0, 0;\n"
                 "wgmma.mma_async.sync.aligned.m64n128k16.f16.f16.f16 " L32 ", {%32,%33,%34,%35}, %36, p, 1, 1, 0;}"
                 : V8(d, 0), V8(d, 8), V8(d, 16), V8(d, 24) : "r"(a[0]), "r"(a[1]), "r"(a[2]), "r"(a[3]), "l"(db));
}
__device__ __forceinline__ void h128(uint32_t* d, const uint32_t* a, uint64_t db) {
    asm volatile("{.reg .pred p; setp.eq.b32 p, 0, 0;\n"
                 "wgmma.mma_async.sync.aligned.m64n128k16.f16.f16.f16 " L32 ", {%32,%33,%34,%35}, %36, p, 1, 1, 0;}"
                 : U8(d, 0), U8(d, 8), U8(d, 16), U8(d, 24) : "r"(a[0]), "r"(a[1]), "r"(a[2]), "r"(a[3]), "l"(db));
}
__device__ __forceinline__ void h128s(uint32_t* d, uint64_t da, uint64_t db) {
    asm volatile("{.reg .pred p; setp.eq.b32 p, 0, 0;\n"
                 "wgmma.mma_async.sync.aligned.m64n128k16.f16.f16.f16 " L32 ", %32, %33, p, 1, 1, 1, 0;}"
                 : U8(d, 0), U8(d, 8), U8(d, 16), U8(d, 24) : "l"(da), "l"(db));
}
__device__ __forceinline__ void r16t(float* d, const uint32_t* a, uint64_t db) {
    asm volatile("{.reg .pred p; setp.eq.b32 p, 0, 0;\n"
                 "wgmma.mma_async.sync.aligned.m64n16k16.f32.f16.f16 {%0,%1,%2,%3,%4,%5,%6,%7}, {%8,%9,%10,%11}, %12, p, 1, 1, 1;}"
                 : R8(d, 0) : "r"(a[0]), "r"(a[1]), "r"(a[2]), "r"(a[3]), "l"(db));
}
__device__ __forceinline__ void q_gemm(float* d, uint64_t da, uint64_t db) {
    asm volatile("{.reg .pred p, q; .reg .b64 a, b; setp.ne.b32 p, 0, 0; setp.eq.b32 q, 0, 0;\n"
                 "wgmma.fence.sync.aligned;\n"
                 "wgmma.mma_async.sync.aligned.m64n96k16.f32.bf16.bf16 " L48 ", %48, %49, p, 1, 1, 1, 0;\n"
                 "add.s64 a, %48, 128; add.s64 b, %49, 2;\n"
                 "wgmma.mma_async.sync.aligned.m64n96k16.f32.bf16.bf16 " L48 ", a, b, q, 1, 1, 1, 0;\n"
                 "add.s64 a, %48, 256; add.s64 b, %49, 4;\n"
                 "wgmma.mma_async.sync.aligned.m64n96k16.f32.bf16.bf16 " L48 ", a, b, q, 1, 1, 1, 0;\n"
                 "add.s64 a, %48, 384; add.s64 b, %49, 6;\n"
                 "wgmma.mma_async.sync.aligned.m64n96k16.f32.bf16.bf16 " L48 ", a, b, q, 1, 1, 1, 0;\n"
                 "wgmma.commit_group.sync.aligned;\n"
                 "wgmma.wait_group.sync.aligned 0;}"
                 : W8(d, 0), W8(d, 8), W8(d, 16), W8(d, 24), W8(d, 32), W8(d, 40)
                 : "l"(da), "l"(db) : "memory");
}
__device__ __forceinline__ void ss64t(float* d, uint64_t da, uint64_t db, int acc) {
    asm volatile("{.reg .pred p; setp.ne.b32 p, %34, 0;\n"
                 "wgmma.mma_async.sync.aligned.m64n64k16.f32.bf16.bf16 " L32 ", %32, %33, p, 1, 1, 0, 1;}"
                 : R8(d, 0), R8(d, 8), R8(d, 16), R8(d, 24)
                 : "l"(da), "l"(db), "r"(acc));
}
template <int NREG> __device__ __forceinline__ void fence_regs(float* d) {
#pragma unroll
    for (int i = 0; i < NREG; i++) asm volatile("" : "+f"(d[i])::"memory");
}
template <int NREG> __device__ __forceinline__ void fence_regs(uint32_t* d) {
#pragma unroll
    for (int i = 0; i < NREG; i++) asm volatile("" : "+r"(d[i])::"memory");
}
__device__ __forceinline__ void ldsm4t(uint32_t* r, uint32_t addr) {
    asm volatile("ldmatrix.sync.aligned.m8n8.x4.trans.shared.b16 {%0,%1,%2,%3}, [%4];"
                 : "=r"(r[0]), "=r"(r[1]), "=r"(r[2]), "=r"(r[3]) : "r"(addr) : "memory");
}
__device__ __forceinline__ void stsm4t(uint32_t addr, uint32_t a, uint32_t b, uint32_t c, uint32_t d) {
    asm volatile("stmatrix.sync.aligned.m8n8.x4.trans.shared.b16 [%0], {%1,%2,%3,%4};" ::"r"(addr), "r"(a), "r"(b), "r"(c), "r"(d) : "memory");
}
__device__ __forceinline__ void cp16(uint32_t s, const void* g) {
    asm volatile("cp.async.cg.shared.global [%0], [%1], 16;" ::"r"(s), "l"(g) : "memory");
}
__device__ __forceinline__ void cp4(uint32_t s, const void* g) {
    asm volatile("cp.async.ca.shared.global [%0], [%1], 4;" ::"r"(s), "l"(g) : "memory");
}
__device__ __forceinline__ void cp16z(uint32_t s, const void* g, uint32_t skip) {
    asm volatile("{.reg .pred p; setp.ne.u32 p, %2, 0; cp.async.cg.shared.global [%0], [%1], 16, p;}" ::"r"(s), "l"(g), "r"(skip) : "memory");
}
__device__ __forceinline__ void cp_commit() { asm volatile("cp.async.commit_group;" ::: "memory"); }
template <int N> __device__ __forceinline__ void cp_wait() { asm volatile("cp.async.wait_group %0;" ::"n"(N) : "memory"); }
__device__ __forceinline__ void cp_wait_all() { asm volatile("cp.async.wait_all;" ::: "memory"); }
__device__ __forceinline__ void mbar_init(uint32_t a, int cnt) { asm volatile("mbarrier.init.shared::cta.b64 [%0], %1;" ::"r"(a), "r"(cnt) : "memory"); }
__device__ __forceinline__ void mbar_arrive(uint32_t a) { asm volatile("mbarrier.arrive.shared::cta.b64 _, [%0];" ::"r"(a) : "memory"); }
__device__ __forceinline__ void mbar_cp_arrive(uint32_t a) { asm volatile("cp.async.mbarrier.arrive.noinc.shared::cta.b64 [%0];" ::"r"(a) : "memory"); }
__device__ __forceinline__ void mbar_wait(uint32_t a, uint32_t parity) {
    asm volatile("{.reg .pred p; .reg .u32 n; mov.u32 n, 0;\n"
                 "MW_%=: mbarrier.try_wait.parity.shared::cta.b64 p, [%0], %1;\n"
                 "@p bra MD_%=;\n"
                 "add.u32 n, n, 1; setp.gt.u32 p, n, 0x100000;\n"
                 "@p trap;\n"
                 "bra MW_%=;\n"
                 "MD_%=: }" ::"r"(a), "r"(parity) : "memory");
}
template <int ID, int CNT> __device__ __forceinline__ void bar_sync()   { asm volatile("bar.sync %0, %1;" ::"n"(ID), "n"(CNT) : "memory"); }
template <int ID, int CNT> __device__ __forceinline__ void bar_arrive() { asm volatile("bar.arrive %0, %1;" ::"n"(ID), "n"(CNT) : "memory"); }
__device__ __forceinline__ float tanh_fast(float x) { float y; asm("tanh.approx.f32 %0, %1;" : "=f"(y) : "f"(x)); return y; }
__device__ __forceinline__ uint32_t pack2(float lo, float hi) {
    uint32_t r; asm("cvt.rn.bf16x2.f32 %0, %1, %2;" : "=r"(r) : "f"(hi), "f"(lo)); return r;
}
__device__ __forceinline__ uint32_t pack2h(float lo, float hi) {
    uint32_t r; asm("cvt.rn.f16x2.f32 %0, %1, %2;" : "=r"(r) : "f"(hi), "f"(lo)); return r;
}
__device__ __forceinline__ float bf_lo(uint32_t v) { return __uint_as_float(v << 16); }
__device__ __forceinline__ float bf_hi(uint32_t v) { return __uint_as_float(v & 0xFFFF0000u); }
__device__ __forceinline__ uint32_t bf2h(uint32_t v) { return pack2h(bf_lo(v), bf_hi(v)); }
__device__ __forceinline__ uint32_t amax2(uint32_t a, uint32_t b) {
    uint32_t r; asm("max.NaN.xorsign.abs.bf16x2 %0, %1, %2;" : "=r"(r) : "r"(a), "r"(b)); return r;
}
__device__ __forceinline__ uint32_t amax_fin(uint32_t m) { return max(m & 0x7FFFu, (m >> 16) & 0x7FFFu); }
__device__ __forceinline__ uint32_t silu_h2(uint32_t h) {
    uint32_t t, s;
    asm("tanh.approx.f16x2 %0, %1;" : "=r"(t) : "r"(h));
    asm("fma.rn.f16x2 %0, %1, %2, %1;" : "=r"(s) : "r"(h), "r"(t));
    return s;
}
__device__ __forceinline__ uint32_t hadd2(uint32_t a, uint32_t b) { uint32_t s; asm("add.rn.f16x2 %0, %1, %2;" : "=r"(s) : "r"(a), "r"(b)); return s; }
__device__ __forceinline__ uint32_t lds32(uint32_t a) { uint32_t v; asm volatile("ld.shared.b32 %0, [%1];" : "=r"(v) : "r"(a) : "memory"); return v; }
__device__ __forceinline__ uint32_t lds16(uint32_t a) { uint32_t v; asm volatile("ld.shared.u16 %0, [%1];" : "=r"(v) : "r"(a) : "memory"); return v; }
__device__ __forceinline__ uint4 lds128(uint32_t a) {
    uint4 v; asm volatile("ld.shared.v4.b32 {%0,%1,%2,%3}, [%4];" : "=r"(v.x), "=r"(v.y), "=r"(v.z), "=r"(v.w) : "r"(a) : "memory"); return v;
}
__device__ __forceinline__ void sts16(uint32_t a, uint32_t v) { asm volatile("st.shared.u16 [%0], %1;" ::"r"(a), "r"(v) : "memory"); }
__device__ __forceinline__ void sts32(uint32_t a, uint32_t v) { asm volatile("st.shared.b32 [%0], %1;" ::"r"(a), "r"(v) : "memory"); }
__device__ __forceinline__ void sts64(uint32_t a, uint32_t x, uint32_t y) { asm volatile("st.shared.v2.b32 [%0], {%1,%2};" ::"r"(a), "r"(x), "r"(y) : "memory"); }
__device__ __forceinline__ void sts128(uint32_t a, uint32_t x, uint32_t y, uint32_t z, uint32_t w) {
    asm volatile("st.shared.v4.b32 [%0], {%1,%2,%3,%4};" ::"r"(a), "r"(x), "r"(y), "r"(z), "r"(w) : "memory");
}
template <uint32_t V> __device__ __forceinline__ uint32_t atoms_add(uint32_t a) {
    uint32_t v; asm volatile("atom.shared.add.u32 %0, [%1], %2;" : "=r"(v) : "r"(a), "n"(V) : "memory"); return v;
}
__device__ __forceinline__ uint2 lds64(uint32_t a) {
    uint2 v; asm volatile("ld.shared.v2.b32 {%0,%1}, [%2];" : "=r"(v.x), "=r"(v.y) : "r"(a) : "memory"); return v;
}
__device__ __forceinline__ void st_rel64(void* p, uint32_t x, uint32_t y) {
    asm volatile("st.relaxed.gpu.global.b64 [%0], %1;" ::"l"(p), "l"((uint64_t)x | ((uint64_t)y << 32)) : "memory");
}
__device__ __forceinline__ uint64_t ld_rel64(const void* p) {
    uint64_t v; asm volatile("ld.relaxed.gpu.global.b64 %0, [%1];" : "=l"(v) : "l"(p) : "memory"); return v;
}
__device__ __forceinline__ uint32_t ld_acq32(const void* p) {
    uint32_t v; asm volatile("ld.acquire.gpu.global.b32 %0, [%1];" : "=r"(v) : "l"(p) : "memory"); return v;
}
__device__ __forceinline__ uint32_t ld_g32(const void* p) {
    uint32_t v; asm volatile("ld.global.b32 %0, [%1];" : "=r"(v) : "l"(p) : "memory"); return v;
}
__device__ __forceinline__ uint4 ld_stream(const void* p) {
    uint4 v;
    asm volatile("ld.global.nc.L1::no_allocate.v4.b32 {%0,%1,%2,%3}, [%4];" : "=r"(v.x), "=r"(v.y), "=r"(v.z), "=r"(v.w) : "l"(p) : "memory");
    return v;
}
__device__ __forceinline__ uint32_t atoms_addr(uint32_t a, uint32_t inc) {
    uint32_t v; asm volatile("atom.shared.add.u32 %0, [%1], %2;" : "=r"(v) : "r"(a), "r"(inc) : "memory"); return v;
}
template <uint32_t LIM, uint32_t BIT> __device__ __forceinline__ void put(uint32_t v, uint32_t w, uint32_t& mask) {
    asm volatile("{.reg .pred q, o; .reg .u32 t; setp.lt.u32 q|o, %1, %3; and.b32 t, %1, 0x3FFFF;\n"
                 "@q st.shared.b32 [t], %2; @o or.b32 %0, %0, %4;}" : "+r"(mask) : "r"(v), "r"(w), "n"(LIM), "n"(BIT) : "memory");
}
template <uint32_t LIM> __device__ __forceinline__ void put(uint32_t v, uint32_t w) {
    asm volatile("{.reg .pred q; .reg .u32 t; setp.lt.u32 q, %0, %2; and.b32 t, %0, 0x3FFFF; @q st.shared.b32 [t], %1;}"
                 ::"r"(v), "r"(w), "n"(LIM) : "memory");
}
__device__ __forceinline__ uint4 ld_rec(const uint4* p) {
    uint4 v;
    asm volatile("ld.relaxed.gpu.global.v4.b32 {%0,%1,%2,%3}, [%4];" : "=r"(v.x), "=r"(v.y), "=r"(v.z), "=r"(v.w) : "l"(p) : "memory");
    return v;
}
__device__ __forceinline__ void bulk_store(void* g, uint32_t s, uint32_t bytes) {
    asm volatile("cp.async.bulk.global.shared::cta.bulk_group [%0], [%1], %2;\n"
                 "cp.async.bulk.commit_group;" ::"l"(g), "r"(s), "r"(bytes) : "memory");
}
__device__ __forceinline__ void bulk_wait()      { asm volatile("cp.async.bulk.wait_group 0;" ::: "memory"); }
__device__ __forceinline__ void l2_prefetch(const void* p, uint32_t bytes) {
    asm volatile("cp.async.bulk.prefetch.L2.global [%0], %1;" ::"l"(p), "r"(bytes) : "memory");
}
__device__ __forceinline__ const char* madw(uint32_t a, uint32_t b, const char* p) {
    const char* r; asm("mad.wide.u32 %0, %1, %2, %3;" : "=l"(r) : "r"(a), "r"(b), "l"(p)); return r;
}
__device__ __forceinline__ uint64_t dsc(uint32_t lo, uint32_t hi) { return (uint64_t)lo | ((uint64_t)hi << 32); }
__device__ __forceinline__ uint32_t dlo(uint32_t addr) { return ((addr & 0x3FFFF) >> 4) | 0x10000u; }
constexpr uint32_t DH128 = (1024 >> 4) | (1u << 30), DH32A = (512 >> 4) | (3u << 30), DH32B = (256 >> 4) | (3u << 30);
__device__ __forceinline__ bool elect() {
    uint32_t r;
    asm volatile("{.reg .pred p; elect.sync _|p, 0xFFFFFFFF; selp.u32 %0, 1, 0, p;}" : "=r"(r));
    return r != 0;
}
__device__ __forceinline__ int node2row(int n) { return ((n >> 3) & 1) * 96 + (n >> 4) * 8 + (n & 7); }
__device__ __forceinline__ int row2node(int r) { return r < 96 ? (r >> 3) * 16 + (r & 7) : ((r - 96) >> 3) * 16 + 8 + (r & 7); }
__device__ __forceinline__ int col2pos(int c) { return (c & ~15) | ((c & 7) << 1) | ((c >> 3) & 1); }

struct Args {
    const __nv_bfloat16 *x, *ea;
    const int *src, *dst;
    const __nv_bfloat16 *w1, *b1, *w2, *b2;
    __nv_bfloat16* out;
    uint4 *ra, *xh;
    uint2* rx;
    uint32_t* ctl;
};

__device__ __forceinline__ void bin_overflow(uint32_t sb, uint32_t rec, uint32_t v) {
    const uint32_t ix = atoms_add<1>(sb + F_XC);
    if (ix < OVC) sts64(sb + SM_OVL + ix * 8, rec, v);
    else sts32(sb + F_BAD, 1u);
}
__device__ __forceinline__ void send_extra(uint32_t sb, uint32_t mask, uint32_t ep, const Args& a) {
#pragma unroll 1
    while (mask) {
        const uint32_t i = __ffs(mask) - 1, off = threadIdx.x * 4 + (3 - (i >> 2)) * 2048 + (i & 3);
        mask &= mask - 1;
        const uint32_t d = a.dst[blockIdx.x * CH + off], b = __umulhi(d, 22605092u);
        const uint32_t ix = atoms_add<1>(sb + SM_STA + b * RP + RS * 4) & 0x1FFFu;
        if (ix < RX) st_rel64(a.rx + (b * G + blockIdx.x) * RX + ix, ((d - b * NPB) << 24) + off, ep);
    }
}
template <int MODE> __device__ __forceinline__ void recv_extra(uint32_t sb, uint32_t n, uint32_t run, uint32_t ep, const Args& a) {
    if (n > RX) { sts32(sb + F_BAD, 1u); n = 0; }
    const uint2* p = a.rx + (blockIdx.x * G + run) * RX;
#pragma unroll 1
    for (uint32_t i = 0; i < n; i++) {
        uint64_t w = ld_rel64(p + i);
        int it = 0;
        while (MODE == 3 && (uint32_t)(w >> 32) != ep) {
            if (++it > (1 << 22)) __trap();
            w = ld_rel64(p + i);
        }
        const uint32_t rec = (uint32_t)w + run * CH, v = atoms_add<CINC>(sb + SM_DEG + (rec >> 24) * 4);
        if (v < BINL) sts32(v & 0x3FFFFu, rec);
        else bin_overflow(sb, rec, v);
    }
}
__device__ __forceinline__ void load_w2(uint32_t sb, int u, int nthr, const Args& a) {
    for (int i = u; i < 128 * 32; i += nthr) {
        const int kp = i >> 5, w = i & 31;
        const int k = (kp & ~15) | ((kp & 1) << 3) | ((kp >> 1) & 7);
        cp4(sb + SM_W2 + kp * 128 + (((w & 7) ^ (kp & 7)) << 4) + (w >> 3) * 4, a.w2 + k * 64 + w * 2);
    }
    if (u < 8) cp16(sb + SM_B2 + u * 16, a.b2 + u * 8);
    cp_wait_all();
}

template <int FAST> __device__ __forceinline__ void tail_gemm(uint32_t sb, int wg, int warp4, int lane, int bucket, __nv_bfloat16* __restrict__ out) {
    const int g = lane >> 2, q = lane & 3;
    float d[32];
#pragma unroll
    for (int i = 0; i < 32; i++) d[i] = 0.f;
    wg_fence();
#pragma unroll
    for (int ks = 0; ks < 8; ks++)
        ss64t(d, mkdesc(sb + SM_QA + (ks >> 2) * 24576 + wg * 8192 + (ks & 3) * 32, 16, 1024, 1),
              mkdesc(sb + SM_W2 + ks * 2048, 16, 1024, 1), ks);
    wg_commit();
    const uint4 bb0 = lds128(sb + SM_B2 + q * 32), bb1 = lds128(sb + SM_B2 + q * 32 + 16);
    const int node0 = row2node(wg * 64 + warp4 * 16 + g);
    const uint32_t dg0 = (lds32(sb + SM_DEG + node0 * 4) >> (18 * FAST)) - FAST, dg1 = (lds32(sb + SM_DEG + node0 * 4 + 64) >> (18 * FAST)) - FAST;
    wg_wait<0>();
    fence_regs<32>(d);
    const uint32_t bw[8] = {bb0.x, bb0.y, bb0.z, bb0.w, bb1.x, bb1.y, bb1.z, bb1.w};
    uint32_t m = 0;
#pragma unroll
    for (int r = 0; r < 2; r++) {
        const int node = node0 + 16 * r;
        const int gn = bucket * NPB + node;
        const uint32_t dg = r ? dg1 : dg0;
        const float fd = (float)dg;
        uint32_t o[8];
#pragma unroll
        for (int j = 0; j < 8; j++) {
            const float v0 = fmaf(fd, bf_lo(bw[j]), d[4 * j + 2 * r]);
            const float v1 = fmaf(fd, bf_hi(bw[j]), d[4 * j + 2 * r + 1]);
            o[j] = dg ? pack2(v0, v1) : 0u;
            m = amax2(m, o[j]);
        }
        if (node < NPB && gn < NN) {
            uint4* op = reinterpret_cast<uint4*>(out + (size_t)gn * 64 + 16 * q);
            op[0] = make_uint4(o[0], o[1], o[2], o[3]);
            op[1] = make_uint4(o[4], o[5], o[6], o[7]);
        }
    }
    if (amax_fin(m) >= 0x7F80u) sts32(sb + F_NF, 1u);
}
__device__ __forceinline__ void tail_scan(uint32_t sb, int u) {
    uint32_t m = 0;
#pragma unroll
    for (int j = 0; j < 6; j++) {
        const int row = (u >> 3) + 32 * j;
        const uint32_t dg = lds32(sb + SM_DEG + row2node(row) * 4) >> 19;
        const uint4 a = lds128(sb + SM_QA + row * 128 + (u & 7) * 16), b = lds128(sb + SM_QA + 24576 + row * 128 + (u & 7) * 16);
        const uint32_t v = amax2(amax2(amax2(a.x, a.y), amax2(a.z, a.w)), amax2(amax2(b.x, b.y), amax2(b.z, b.w)));
        if (dg) m = amax2(m, v);
    }
    const float thr = (float)lds32(sb + F_DMAX) * (1.f / 32768.f) * fmaf(88.f, bf_lo(lds32(sb + F_WMAX)), 30.f);
    if (bf_lo(amax_fin(m)) >= thr) sts32(sb + F_BIG, 1u);
}
__device__ __forceinline__ bool tail_failed(uint32_t sb) {
    bar_sync<1, NT>();
    return lds32(sb + F_NF) != 0 || lds32(sb + F_BIG) == 0;
}

__device__ __forceinline__ void slow_path(uint32_t sb, int bucket, const Args& a) {
    const int tid = threadIdx.x, lane = tid & 31, j = tid & 127, wg = tid >> 7;
    bar_sync<0, NT>();
    for (int i = tid; i < NPB * 128; i += NT) sts32(sb + SM_SAGG + i * 4, 0u);
    if (tid < 192) sts32(sb + SM_DEG + tid * 4, 0u);
    const unsigned short* w1u = reinterpret_cast<const unsigned short*>(a.w1);
    {
        uint32_t w[32];
#pragma unroll
        for (int k = 0; k < 32; k++) w[k] = w1u[(64 + 2 * k) * 128 + j] | ((uint32_t)w1u[(65 + 2 * k) * 128 + j] << 16);
        const float bj = __bfloat162float(a.b1[j]);
        for (int node = wg; node < NPB && bucket * NPB + node < NN; node += 5) {
            const uint4* xr = reinterpret_cast<const uint4*>(a.x + (size_t)(bucket * NPB + node) * 64);
            float h = bj;
            fence_regs<32>(w);
#pragma unroll
            for (int k = 0; k < 8; k++) {
                const uint4 v = __ldg(xr + k);
                const uint32_t vv[4] = {v.x, v.y, v.z, v.w};
#pragma unroll
                for (int i = 0; i < 4; i++) {
                    h = fmaf(bf_lo(vv[i]), bf_lo(w[4 * k + i]), h);
                    h = fmaf(bf_hi(vv[i]), bf_hi(w[4 * k + i]), h);
                }
            }
            sts32(sb + SM_SQ + (node * 128 + j) * 4, __float_as_uint(h));
        }
    }
    uint32_t w[40];
#pragma unroll
    for (int k = 0; k < 40; k++) {
        const int r = k < 32 ? 2 * k : 2 * k + 64;
        w[k] = w1u[r * 128 + j] | ((uint32_t)w1u[(r + 1) * 128 + j] << 16);
    }
    bar_sync<0, NT>();
    for (int e0 = wg * 32; e0 < NE; e0 += 160) {
        const int dn = a.dst[e0 + lane] - bucket * NPB;
        unsigned m = __ballot_sync(0xFFFFFFFFu, dn >= 0 && dn < NPB);
        while (m) {
            const int l = __ffs(m) - 1;
            m &= m - 1;
            const int node = __shfl_sync(0xFFFFFFFFu, dn, l);
            const int e = e0 + l;
            const uint4* xr = reinterpret_cast<const uint4*>(a.x + (size_t)a.src[e] * 64);
            const uint4* er = reinterpret_cast<const uint4*>(a.ea + (size_t)e * 16);
            float h = __uint_as_float(lds32(sb + SM_SQ + (node * 128 + j) * 4));
            fence_regs<40>(w);
#pragma unroll
            for (int k = 0; k < 10; k++) {
                const uint4 v = (k < 8) ? __ldg(xr + k) : __ldg(er + (k - 8));
                const uint32_t vv[4] = {v.x, v.y, v.z, v.w};
#pragma unroll
                for (int i = 0; i < 4; i++) {
                    h = fmaf(bf_lo(vv[i]), bf_lo(w[4 * k + i]), h);
                    h = fmaf(bf_hi(vv[i]), bf_hi(w[4 * k + i]), h);
                }
            }
            h *= 0.5f;
            const float f = fmaf(h, tanh_fast(h), h);
            asm volatile("red.shared.add.f32 [%0], %1;" ::"r"(sb + SM_SAGG + (node * 128 + j) * 4), "f"(f) : "memory");
            if (j == 0) atoms_add<1>(sb + SM_DEG + node * 4);
        }
    }
    bar_sync<0, NT>();
    load_w2(sb, tid, NT, a);
    for (int i = tid; i < NPB * 64; i += NT) {
        const int node = i >> 6, pr = i & 63;
        const int hid = (pr >> 3) * 16 + (pr & 7);
        const float u = __uint_as_float(lds32(sb + SM_SAGG + (node * 128 + hid) * 4));
        const float v = __uint_as_float(lds32(sb + SM_SAGG + (node * 128 + hid + 8) * 4));
        const int ch = (pr & 31) >> 2;
        sts32(sb + SM_QA + (pr >> 5) * 24576 + node2row(node) * 128 + ((ch ^ (node & 7)) << 4) + (pr & 3) * 4, pack2(u, v));
    }
    fence_async();
    bar_sync<0, NT>();
    if (wg < 3) tail_gemm<0>(sb, wg, (tid >> 5) & 3, lane, bucket, a.out);
}

template <int MODE>
__device__ __forceinline__ bool producer(uint32_t sb, const Args& a) {
    const int tid = threadIdx.x, lane = tid & 31, warp = tid >> 5, warp4 = warp & 3, u = tid - 512;
    const int cta = blockIdx.x;
    const int nrow = min(NPB, NN - cta * NPB);
    asm volatile("setmaxnreg.dec.sync.aligned.u32 64;");
    uint32_t ep = 0;
    if (MODE == 3) ep = ld_g32(a.ctl + 32 + 32 * cta);
    auto load_w1 = [&](int j0, int j1) {
        const int r = u >> 4, c = u & 15;
        const uint32_t sw = r * 128 + (((c & 7) ^ r) << 4);
        const __nv_bfloat16* wp = a.w1 + u * 8;
#pragma unroll
        for (int j = j0; j < j1; j++) {
            const uint32_t d = j < 8 ? SM_W1A + j * 1024 : j < 16 ? SM_W1B + (j - 8) * 1024 : SM_W1A + (j - 8) * 1024;
            cp16(sb + d + (c >> 3) * (j < 8 || j >= 16 ? 10240 : 8192) + sw, wp + j * 1024);
        }
    };
    if (MODE & 2) {
        if (W1AT == 0) load_w1(0, 18);
        if (W1AT == 3) load_w1(8, 16);
        if (u < 16) cp16(sb + SM_B1 + u * 16, a.b1 + u * 8);
        if (u == 32) {
#pragma unroll
            for (int i = 0; i < 4; i++) {
                mbar_init(sb + SM_BAR + i * 8, 128 + 4);
                mbar_init(sb + SM_BAR + 32 + i * 8, 8);
            }
        }
        if (u == 64 && cta == G - 1) { l2_prefetch(a.w2, 16384); l2_prefetch(a.b2, 128); }
    }
    bar_sync<9, 160>();
    {
        const int xrow = u >> 3;
        const uint32_t xa = sb + SM_XO + xrow * 128 + (((u & 7) ^ (xrow & 7)) << 4);
        const __nv_bfloat16* xp = a.x + (size_t)cta * NPB * 64 + (u & 7) * 8;
#pragma unroll
        for (int j = 0; j < 12; j++) cp16z(xa + j * 2048, xp + min(xrow + 16 * j, nrow - 1) * 64, xrow + 16 * j >= nrow);
        if (MODE & 2) {
            if (W1AT == 1) load_w1(0, 18);
            if (W1AT == 2) load_w1(8, 16);
            mbar_cp_arrive(sb + B_X);
        }
        cp_commit();
        if ((MODE & 2) && W1AT >= 2) { load_w1(0, 8); load_w1(16, 18); }
        cp_commit();
        cp_wait<1>();
        CSTAMP(20, u == 0);
        if ((MODE & 2) && u == 0) l2_prefetch(a.src + cta * CH, min(CH, NE - cta * CH) * 4);
        __syncwarp();
        if (MODE & 1) {
#pragma unroll
            for (int j = 0; j < 12; j++) {
                const uint4 v = lds128(xa + j * 2048);
                sts128(sb + SM_XR + u * 16 + j * 2048, bf2h(v.x), bf2h(v.y), bf2h(v.z), bf2h(v.w));
            }
            fence_async();
        }
        cp_wait_all();
    }
    bar_sync<10, 128>();
    CSTAMP(16, u == 0);
    if (MODE == 3 && warp == 19) bar_sync<4, 64>();
    if ((MODE & 1) && u == 96) {
        bulk_store(a.xh + (size_t)cta * NPB * 8, sb + SM_XR, min(NPB, nrow + 1) * 128);
        if (MODE == 3) a.ctl[32 + 32 * cta] = ++ep;
        bulk_wait();
        CSTAMP(5, true);
        if (MODE == 3) {
            asm volatile("red.release.gpu.global.add.u32 [%0], 1;" ::"l"(a.ctl) : "memory");
            int it = 0;
            while ((int)(ld_acq32(a.ctl) - ep * G) < 0)
                if (++it > (1 << 22)) __trap();
        }
        CSTAMP(13, true);
    }
    if (!(MODE & 2)) return false;
    if (u < 80) {
        uint32_t m = 0;
#pragma unroll
        for (int c = 0; c < 16; c++) {
            const uint4 v = lds128(sb + SM_W1A + (c >> 3) * 10240 + u * 128 + (((c & 7) ^ (u & 7)) << 4));
            m = amax2(m, amax2(amax2(v.x, v.y), amax2(v.z, v.w)));
        }
        m = amax_fin(m);
        if (m != 0 && m < 0x3A00u) sts32(sb + F_BAD, 1u);
        asm volatile("red.shared.max.u32 [%0], %1;" ::"r"(sb + F_WMAX), "r"(m) : "memory");
    }
    const char* xb = reinterpret_cast<const char*>(a.xh) + (lane & 7) * 16;
    const char* eb = reinterpret_cast<const char*>(a.ea) + (lane & 1) * 16;
    const int oc = warp4 * 32 + lane;
    const uint32_t posa = sb + SM_POS + col2pos(oc) * 2;
    auto lookup = [&](int t) { return lds32(sb + SM_BIN + lds16(posa + t * 256)); };
    const uint32_t raw = sb + SM_RAW + u * 16, sring = sb + SM_SR + oc * 4;
    auto fetch_s = [&](int slot, uint32_t rec) {
        if (rec & PADW) sts32(sring + slot * 512, NN);
        else cp4(sring + slot * 512, madw(rec & 0xFFFFFu, 4u, reinterpret_cast<const char*>(a.src)));
    };
    auto fetch_e = [&](int slot, uint32_t rec) {
        const uint32_t l0 = __shfl_sync(0xFFFFFFFFu, rec, lane >> 1), l1 = __shfl_sync(0xFFFFFFFFu, rec, 16 + (lane >> 1));
        cp16z(raw + slot * 4096, madw(l0 & 0xFFFFFu, 32u, eb), l0 & PADW);
        cp16z(raw + slot * 4096 + 2048, madw(l1 & 0xFFFFFu, 32u, eb), l1 & PADW);
    };
    auto fetch = [&](int slot, uint32_t rec) { fetch_s(slot, rec); fetch_e(slot, rec); };
    const int xc0 = warp4 * 32 + (lane >> 4) * 16 + ((lane >> 3) & 1) * 4;
    const uint32_t slist = sb + SM_SR + xc0 * 4;
    uint32_t xoff[4];
#pragma unroll
    for (int i = 0; i < 4; i++) xoff[i] = sb + SM_XE + (xc0 + i) * 128 + (((lane & 7) ^ ((xc0 + i) & 7)) << 4);
    const int ec = warp4 * 32 + (lane >> 1);
    const uint32_t eoff = sb + SM_XE + 16384 + ec * 32 + (((lane & 1) ^ ((ec >> 2) & 1)) << 4);
    const uint32_t ioff = sb + SM_IND + oc * 32 + (((oc >> 2) & 1) << 4);
    auto put_x = [&](const uint4& la, const uint4& lb, uint32_t so, uint32_t bar) {
        const uint32_t lw[8] = {la.x, la.y, la.z, la.w, lb.x, lb.y, lb.z, lb.w};
#pragma unroll
        for (int i = 0; i < 4; i++) {
            cp16(xoff[i] + so, madw(lw[i], 128u, xb));
            cp16(xoff[i] + so + 1024, madw(lw[4 + i], 128u, xb));
        }
        mbar_cp_arrive(bar);
    };
    auto put_e = [&](const uint32_t* ef, uint32_t cur, uint32_t so, uint32_t ia, uint32_t bar) {
        sts128(eoff + so, ef[0], ef[1], ef[2], ef[3]);
        sts128(eoff + so + 512, ef[4], ef[5], ef[6], ef[7]);
        sts128(ia, 0u, 0u, 0u, 0u);
        sts128(ia ^ 16, 0u, 0u, 0u, 0u);
        if (!(cur & PADW)) sts16(ia ^ ((cur >> 23) & 30u), 0x3C00u);
        __syncwarp();
        if (lane == 0) mbar_arrive(bar);
    };
    __syncwarp();
    bar_sync<5, NT>();
    const int T = lds32(sb + F_BAD) ? 0 : ((int)lds32(sb + F_TOT) + 63) >> 6;
    CSTAMP(17, u == 0 && T >= 0);
    const int T0 = (T + 1) >> 1, T1 = T >> 1;
    uint32_t own[4] = {PADW, PADW, PADW, PADW};
    if (T > 0) own[0] = lookup(0);
    if (T > 1) own[1] = lookup(T - 1);
    fetch_s(0, own[0]);
    fetch_s(1, own[1]);
    cp_commit();
    fetch_e(0, own[0]);
    fetch_e(1, own[1]);
    cp_commit();
    if (T > 2) own[2] = lookup(1);
    if (T > 3) own[3] = lookup(T - 2);
    CSTAMP(18, u == 0);
    bar_sync<6, NT>();
    if (lds32(sb + F_BAD)) {
        cp_wait_all();
        asm volatile("setmaxnreg.inc.sync.aligned.u32 96;");
        return true;
    }
    if (T > 0) {
        cp_wait<1>();
        __syncwarp();
        CSTAMP(21, u == 0);
#pragma unroll
        for (int s = 0; s < 2; s++)
            if (s < T) put_x(lds128(slist + s * 512), lds128(slist + s * 512 + 32), s * XE_S, sb + SM_BAR + s * 16);
        fetch(2, own[2]);
        cp_commit();
        fetch(3, own[3]);
        cp_commit();
        uint32_t nx[2] = {PADW, PADW};
        if (T > 4) nx[0] = lookup(2);
        if (T > 5) nx[1] = lookup(T - 3);
        cp_wait<2>();
#pragma unroll
        for (int s = 0; s < 2; s++) {
            const uint4 e0 = lds128(raw + s * 4096), e1 = lds128(raw + s * 4096 + 2048);
            const uint32_t ef[8] = {bf2h(e0.x), bf2h(e0.y), bf2h(e0.z), bf2h(e0.w), bf2h(e1.x), bf2h(e1.y), bf2h(e1.z), bf2h(e1.w)};
            if (s < T) put_e(ef, own[s], s * XE_S, ioff + s * 4096, sb + SM_BAR + s * 16);
        }
#pragma unroll
        for (int s = 0; s < 2; s++) {
            if (T > 4 + s) fetch(s, nx[s]);
            cp_commit();
            own[s] = own[2 + s];
            own[2 + s] = nx[s];
        }
    }
    int i3 = 8192;
    for (int k = 1; k < T0; k++) {
#pragma unroll
        for (int s = 0; s < 2; s++) {
            if (s == 1 && k >= T1) break;
            const int tn = s ? T - 3 - k : k + 2, st = 2 * s + (k & 1), slot = 2 * (k & 1) + s;
            const bool more = k + 2 < (s ? T1 : T0);
            const uint32_t cur = own[s];
            own[s] = own[2 + s];
            if (more) own[2 + s] = lookup(tn);
            cp_wait<3>();
            __syncwarp();
            const uint4 la = lds128(slist + slot * 512), lb = lds128(slist + slot * 512 + 32);
            const uint4 e0 = lds128(raw + slot * 4096), e1 = lds128(raw + slot * 4096 + 2048);
            const uint32_t ef[8] = {bf2h(e0.x), bf2h(e0.y), bf2h(e0.z), bf2h(e0.w), bf2h(e1.x), bf2h(e1.y), bf2h(e1.z), bf2h(e1.w)};
            const uint32_t ia = ioff + i3 + s * 4096;
            const uint32_t so = s * XE_S + (k & 1) * XE_P;
            mbar_wait(sb + SM_BAR + 32 + st * 8, ((k >> 1) & 1) ^ 1);
            put_x(la, lb, so, sb + SM_BAR + st * 8);
            put_e(ef, cur, so, ia, sb + SM_BAR + st * 8);
            if (more) fetch(slot, own[2 + s]);
            cp_commit();
        }
        i3 = (i3 == 16384) ? 0 : i3 + 8192;
    }
    cp_wait_all();
    bar_sync<10, 128>();
    load_w2(sb, u, 128, a);
    fence_async();
    bar_sync<1, NT>();
    tail_scan(sb, u + 128);
    if (!tail_failed(sb) || T == 0) return false;
    asm volatile("setmaxnreg.inc.sync.aligned.u32 96;");
    return true;
}

template <int MODE>
__device__ __forceinline__ bool consumer(uint32_t sb, const Args& a) {
    const int tid = threadIdx.x, lane = tid & 31, warp = tid >> 5, wg = tid >> 7, warp4 = warp & 3;
    const int cta = blockIdx.x;
    uint32_t ep = 1;
    {
        const int nv = min(CH, NE - cta * CH) >> 2;
        uint4 dv[3];
        if (MODE == 3) ep = ld_g32(a.ctl + 32 + 32 * cta);
        if (MODE & 1) {
            const int* dp = a.dst + cta * CH + tid * 4;
            dv[0] = ld_stream(dp);
            dv[1] = ld_stream(dp + 2048);
            dv[2] = ld_stream(tid + 1024 < nv ? dp + 4096 : dp);
        }
        if (tid == 0) mbar_init(sb + B_X, 128);
        if (tid >= 8 && tid < 16) sts32(sb + SM_FLAG + (tid - 8) * 4, 0u);
        if (tid == 16) sts32(sb + SM_BIN + PADO, PADW);
        __syncwarp();
        if ((XAT < 0 || !(MODE & 1)) && warp == 0) bar_arrive<9, 160>();
        if (tid >= 64 && tid < 288)
            sts32(sb + SM_DEG + (tid - 64) * 4, tid >= 256 ? 0xC0000000u : (1u << 18) + sb + SM_BIN + (tid - 64 < NPB ? (tid - 64) * BINP : PADO));
        else if (tid >= 288 && tid < 288 + G) sts32(sb + SM_CNT + (tid - 288) * 4, sb + SM_STA + (tid - 288) * RP);
        uint32_t pw[5];
#pragma unroll
        for (int j = 0; j < 5; j++) pw[j] = 0xC0000000u + (((tid + RU * (cta - __umulhi(tid + 512 * j, 226050911u))) & 31u) << 24);
        if (MODE == 3) ep++;
        const uint32_t tg = (ep & 511u) << 13;
        if (MODE & 1) {
#pragma unroll
            for (int j = 0; j < 5; j++)
                if (tid + 512 * j < G * RU) sts128(sb + SM_STA + tid * 16 + j * 8192, tg | pw[j], tg | pw[j], tg | pw[j], tg | pw[j]);
        }
        CSTAMP(22, tid == 0);
        bar_sync<2, 512>();
        if (MODE & 1) {
            uint32_t mask = 0, inc = CINC;
            asm volatile("" : "+r"(inc));
#pragma unroll
            for (int j = 0; j < 3; j++)
                if (j < 2 || tid + 1024 < nv) {
                    const uint32_t dd[4] = {dv[j].x, dv[j].y, dv[j].z, dv[j].w};
                    uint32_t w[4], pa[4];
#pragma unroll
                    for (int k = 0; k < 4; k++) {
                        const uint32_t b = __umulhi(dd[k], 22605092u);
                        pa[k] = atoms_addr(sb + SM_CNT + b * 4, inc);
                        w[k] = (dd[k] << 24) + (tg + tid * 4 + j * 2048 + k) - b * ((uint32_t)NPB << 24);
                    }
                    if (j == XAT && warp == 0) bar_arrive<9, 160>();
                    if (j == 0) CSTAMP(2, tid == 0);
                    put<RUNL, 1u>(pa[0], w[0], mask);
                    put<RUNL, 2u>(pa[1], w[1], mask);
                    put<RUNL, 4u>(pa[2], w[2], mask);
                    put<RUNL, 8u>(pa[3], w[3], mask);
                    mask <<= 4;
                }
            if (__builtin_expect(mask != 0, 0)) send_extra(sb, tid + 1024 < nv ? mask : mask << 4, ep, a);
            CSTAMP(3, tid == 0);
            fence_async();
            __syncwarp();
            bar_sync<2, 512>();
            if (tid == 0) {
                bulk_store(a.ra + (size_t)cta * (G * RU), sb + SM_STA, G * RP);
                if (MODE == 1) bulk_wait();
            }
            __syncwarp();
            if (MODE == 3 && warp == 0) bar_arrive<4, 64>();
        }
    }
    if (!(MODE & 2)) return false;
    asm volatile("setmaxnreg.inc.sync.aligned.u32 104;");
    CSTAMP(4, tid == 0);
    mbar_wait(sb + B_X, 0);
    CSTAMP(14, tid == 0);
    const int s = wg >> 1, h = wg & 1;
    fence_async();
    {
        float d[48];
        const float ba = 0.5f * bf_lo(lds16(sb + SM_B1 + (h * 64 + warp4 * 16 + (lane >> 2)) * 2));
        const float bb = 0.5f * bf_lo(lds16(sb + SM_B1 + (h * 64 + warp4 * 16 + (lane >> 2)) * 2 + 16));
        q_gemm(d, mkdesc(sb + SM_W1B + h * 8192, 16, 1024, 1), mkdesc(sb + SM_XO + s * 12288, 16, 1024, 1));
        const uint32_t qa = sb + SM_QA + h * 24576 + (lane >> 4) * 12288 + s * 6144 + (lane & 7) * 128 +
                            (((2 * warp4 + ((lane >> 3) & 1)) ^ (lane & 7)) << 4);
#pragma unroll
        for (int j = 0; j < 6; j++) {
            const float* e = d + 8 * j;
            stsm4t(qa + j * 1024, pack2h(fmaf(e[0], 0.5f, ba), fmaf(e[1], 0.5f, ba)), pack2h(fmaf(e[2], 0.5f, bb), fmaf(e[3], 0.5f, bb)),
                   pack2h(fmaf(e[4], 0.5f, ba), fmaf(e[5], 0.5f, ba)), pack2h(fmaf(e[6], 0.5f, bb), fmaf(e[7], 0.5f, bb)));
        }
    }
    fence_async();
    CSTAMP(19, tid == 0);

    {
        const uint32_t tg = (ep & 511u) << 13;
        const uint4* ga[5];
        uint32_t c0[5];
#pragma unroll
        for (int j = 0; j < 5; j++) {
            const uint32_t i = min(tid + 512 * j, G * RU - 1), run = __umulhi(i, 226050911u);
            ga[j] = a.ra + (run * ((G - 1) * RU) + cta * RU + i);
            c0[j] = run * CH - tg;
        }
        if (MODE == 3) {
            if (tid == 0) bulk_wait();
            __syncwarp();
            bar_sync<2, 512>();
        }
        CSTAMP(24, tid == 0);
        uint4 rv[5], v[5];
        uint32_t inc = CINC;
        asm volatile("" : "+r"(inc));
#pragma unroll
        for (int j = 0; j < 5; j++) rv[j] = ld_rec(ga[j]);
        const uint32_t pw = tg + 0xC0000000u + (lane << 24);
        int mx = 0;
        bool ext = false;
#pragma unroll
        for (int j = 0; j < 5; j++) {
            if (MODE == 3) {
                int it = 0;
                while (__builtin_expect(__any_sync(0xFFFFFFFFu, ((rv[j].x ^ tg) | (rv[j].y ^ tg) | (rv[j].z ^ tg) | (rv[j].w ^ tg)) & TAGM), 0)) {
                    if (++it > (1 << 22)) __trap();
                    rv[j] = ld_rec(ga[j]);
                }
            }
            if (j == 0) CSTAMP(23, tid == 0);
            if (j == 4 && tid + 2048 >= G * RU) rv[4].x = rv[4].y = rv[4].z = rv[4].w = pw;
            v[j].x = atoms_addr(sb + SM_DEG + (rv[j].x >> 22), inc);
            v[j].y = atoms_addr(sb + SM_DEG + (rv[j].y >> 22), inc);
            v[j].z = atoms_addr(sb + SM_DEG + (rv[j].z >> 22), inc);
            v[j].w = atoms_addr(sb + SM_DEG + (rv[j].w >> 22), inc);
            ext |= (rv[j].w ^ pw) - 1u < 0x1FFFu;
            put<BINL>(v[j].x, rv[j].x + c0[j]);
            put<BINL>(v[j].y, rv[j].y + c0[j]);
            put<BINL>(v[j].z, rv[j].z + c0[j]);
            put<BINL>(v[j].w, rv[j].w + c0[j]);
            mx = max(max(mx, max((int)v[j].x, (int)v[j].y)), max((int)v[j].z, (int)v[j].w));
        }
        uint32_t m = __ballot_sync(0xFFFFFFFFu, mx >= (int)BINL || ext);
#pragma unroll 1
        while (__builtin_expect(m != 0, 0)) {
            const int l = __ffs(m) - 1;
            const uint32_t sc = sb + SM_STA + warp * 160;
            m &= m - 1;
            if (lane == l) {
#pragma unroll
                for (int j = 0; j < 5; j++) {
                    sts128(sc + j * 16, rv[j].x, rv[j].y, rv[j].z, rv[j].w);
                    sts128(sc + 80 + j * 16, v[j].x, v[j].y, v[j].z, v[j].w);
                }
            }
            __syncwarp();
            if (lane < 20) {
                const uint32_t w = lds32(sc + lane * 4), c = lds32(sc + 80 + lane * 4);
                const uint32_t run = __umulhi(warp * 32 + l + 512 * (lane >> 2), 226050911u);
                if ((int)c >= (int)BINL) bin_overflow(sb, w + run * CH - tg, c);
                if ((w ^ (tg + 0xC0000000u + (l << 24))) - 1u < 0x1FFFu) recv_extra<MODE>(sb, w & 0x1FFFu, run, ep, a);
            }
            __syncwarp();
        }
    }
    CSTAMP(7, tid == 0);
    bar_sync<2, 512>();
    int T;
    {
        uint32_t c[6], tot = 0, bef = 0;
#pragma unroll
        for (int j = 0; j < 6; j++) c[j] = lds32(sb + SM_DEG + lane * 4 + j * 128) >> 19;
        const uint32_t own = lds32(sb + SM_DEG + min(warp * 12 + lane, 191) * 4);
        const uint32_t bad = lds32(sb + F_BAD), no = lds32(sb + F_XC);
        CSTAMP(6, tid == 0 && own != 1);
#pragma unroll
        for (int j = 0; j < 6; j++) {
            tot += c[j];
            if (lane + 32 * j < warp * 12) bef += c[j];
        }
        uint32_t inc = own >> 19;
#pragma unroll
        for (int o = 1; o < 16; o <<= 1) {
            const uint32_t w = __shfl_up_sync(0xFFFFFFFFu, inc, o);
            if (lane >= o) inc += w;
        }
        tot = __reduce_add_sync(0xFFFFFFFFu, tot);
        bef = __reduce_add_sync(0xFFFFFFFFu, bef);
        const uint32_t pk = ((bef + inc - (own >> 19)) << 16) + (own >> 18);
        T = (tot + 63) >> 6;
        if (bad == 0 && tot <= CAP / 2) {
            if (lane < 12 && own < BINL + (1u << 18)) sts32(own & 0x3FFFFu, PADW);
            const int l8 = lane & 7;
            const uint32_t val = ((warp * 12 + (lane >> 3)) * BINP + l8 * 8) * 0x10001u + 0x40000u;
#pragma unroll
            for (int r = 0; r < 3; r++) {
                const uint32_t e = __shfl_sync(0xFFFFFFFFu, pk, 4 * r + (lane >> 3));
                const uint32_t ad = sb + SM_POS + (e >> 16) * 4 + l8 * 4, lim = (e & 0xFFFFu) - 2 * l8;
#pragma unroll
                for (int i = 0; i < 3; i++)
                    if ((int)lim > 16 * i + 1) sts32(ad + 32 * i, val + (uint32_t)(r * 4 * BINP + 64 * i) * 0x10001u);
            }
            if (tid < 64 && tot + tid < T * 64) sts32(sb + SM_POS + (tot + tid) * 4, PADO * 0x10001u);
            if (no) {
                if (lane < 12 && own >= BINL && !(own & (1u << 18))) sts16(sb + SM_POS + (pk >> 16) * 4 + (pk & 0xFFFFu) * 2 - 2, PADO);
#pragma unroll 1
                for (uint32_t i = 0; i < no; i += 32) {
                    const uint2 o = lds64(sb + SM_OVL + min(i + lane, OVC - 1u) * 8);
                    const uint32_t n = (o.x >> 24) - warp * 12, e = __shfl_sync(0xFFFFFFFFu, pk, n);
                    if (i + lane < no && n < 12) sts16(sb + SM_POS + (e >> 16) * 4 + (o.y >> 18) * 2 - 2, OVLO + (i + lane) * 8);
                }
            }
        } else if (tid == 0) sts32(sb + F_BAD, 1u);
        if (tid == 0) sts32(sb + F_TOT, tot);
        __syncwarp();
        bar_sync<5, NT>();
        CSTAMP(8, tid == 0);
        if (tid < T && lds32(sb + F_BAD) == 0) {
            const int T0 = (T + 1) >> 1;
            const uint32_t first = lds32(sb + SM_BIN + lds16(sb + SM_POS + tid * 256)) >> 24;
            const uint32_t last = lds32(sb + SM_BIN + lds16(sb + SM_POS + min(tid * 64u + 63u, tot - 1) * 4)) >> 24;
            const uint32_t w = min(first >> 3, 22u), ta = sb + SM_TT + (tid < T0 ? tid : 32 + T - 1 - tid) * 16;
            sts32(ta + 4, dlo(sb + SM_QA + ((w + 1) >> 1) * 1024));
            sts32(ta + 8, ((12288 - (w & 1) * 1024) >> 4) | (1u << 30));
            sts32(ta, (tid < T0 ? first : last) * 64);
            if (tid == T0) {
                sts32(sb + SM_TT + T0 * 16, first * 64);
                sts32(sb + SM_TT + (32 + T - T0) * 16, first * 64);
            }
            if (T == 1) sts32(sb + SM_TT + 16, NPB * 64);
            if ((last >> 3) > w + 1) sts32(sb + F_BAD, 1u);
        }
        if (warp == 2) {
            const uint32_t m = __reduce_max_sync(0xFFFFFFFFu, max(max(max(c[0], c[1]), max(c[2], c[3])), max(c[4], c[5])));
            if (lane == 0) sts32(sb + F_DMAX, 2 * m);
        }
        __syncwarp();
    }
    uint32_t w1f[5][4];
    {
        const int kr = (lane & 7) + 8 * (lane >> 4), ch = 2 * warp4 + ((lane >> 3) & 1);
#pragma unroll
        for (int ks = 0; ks < 5; ks++) {
            ldsm4t(w1f[ks], sb + SM_W1A + h * 10240 + (16 * ks + kr) * 128 + ((ch ^ (kr & 7)) << 4));
#pragma unroll
            for (int i = 0; i < 4; i++) w1f[ks][i] = pack2h(0.5f * bf_lo(w1f[ks][i]), 0.5f * bf_hi(w1f[ks][i]));
        }
    }
    bar_sync<6, NT>();
    if (lds32(sb + F_BAD)) {
        asm volatile("setmaxnreg.dec.sync.aligned.u32 96;");
        return true;
    }

    {
        const int wgu = __shfl_sync(0xFFFFFFFFu, wg, 0), Tu = __shfl_sync(0xFFFFFFFFu, T, 0);
        const int su = wgu >> 1, hu = wgu & 1;
        const int Ts = su ? Tu >> 1 : (Tu + 1) >> 1;
        if (Ts > 0) {
            const int q = lane & 3;
            const uint32_t a0 = q * 256 + (((2 * warp4 + (lane >> 4)) ^ (2 * q)) << 4) + ((lane >> 2) & 3) * 4, a1 = (a0 + 128) ^ 16;
            const uint32_t c0 = sb + SM_QA + hu * 24576 + (su ? 0 : 960) - 128 * q;
            uint32_t acc[32], pk[16], fa[4];
            float agg[8];
#pragma unroll
            for (int i = 0; i < 8; i++) agg[i] = 0.f;
#pragma unroll
            for (int i = 0; i < 16; i++) pk[i] = 0u;
            auto flush = [&](uint32_t F, bool on) {
                const uint32_t v = F + c0;
#pragma unroll
                for (int j = 0; j < 4; j++) {
                    const int i0 = (j >> 1) * 4 + (j & 1);
                    const uint32_t t = v - 64 * (j & 1) - 512 * (j >> 1);
                    if (on && ((t ^ fa[j]) & ~1023u)) {
                        sts32(fa[j] + (j >> 1) * 12288, pack2(agg[i0], agg[i0 + 2]));
                        agg[i0] = 0.f;
                        agg[i0 + 2] = 0.f;
                    }
                    asm("lop3.b32 %0, %1, %0, 1023, 0xD8;" : "+r"(fa[j]) : "r"(t));
                }
            };
            fa[0] = fa[2] = a0;
            fa[1] = fa[3] = a1;
            const uint32_t tta = sb + SM_TT + su * 512;
            uint4 tt = lds128(tta);
            flush(tt.x, false);
            const uint32_t ifirst = dlo(sb + SM_IND + su * 4096), ilast = ifirst + 1024;
            uint32_t iprev = ifirst, icur = ifirst;
            const uint32_t x0 = dlo(sb + SM_XE + su * XE_S), bar0 = sb + SM_BAR + 2 * su * 8;
            for (int k = 0; k < Ts; k++) {
                const uint32_t dx = x0 + (k & 1) * (XE_P >> 4), bar = bar0 + (k & 1) * 8;
                mbar_wait(bar, (k >> 1) & 1);
                CSTAMP(9, tid == 0 && k == 0);
                fence_async();
                wg_fence();
#pragma unroll
                for (int kk = 0; kk < 4; kk++) r16t(agg, pk + 4 * kk, dsc(iprev + kk * 64, DH32A));
                wg_commit();
                h128z(acc, w1f[0], dsc(dx, DH128));
                h128(acc, w1f[1], dsc(dx + 2, DH128));
                h128(acc, w1f[2], dsc(dx + 4, DH128));
                h128(acc, w1f[3], dsc(dx + 6, DH128));
                h128(acc, w1f[4], dsc(dx + 1024, DH32B));
                h128s(acc, dsc(tt.y + hu * 1536, tt.z), dsc(icur, DH32B));
                wg_commit();
                wg_wait<1>();
                fence_regs<8>(agg);
                fence_regs<16>(pk);
                flush(tt.x, true);
                tt = lds128(tta + (k + 1) * 16);
                wg_wait<0>();
                fence_regs<32>(acc);
                if (elect()) mbar_arrive(bar + 32);
#pragma unroll
                for (int i = 0; i < 16; i++) {
                    const int i0 = (i >> 1) * 4 + (i & 1);
                    pk[i] = hadd2(silu_h2(acc[i0]), silu_h2(acc[i0 + 2]));
                }
                fence_regs<16>(pk);
                iprev = icur;
                icur = icur == ilast ? ifirst : icur + 512;
            }
            wg_fence();
#pragma unroll
            for (int kk = 0; kk < 4; kk++) r16t(agg, pk + 4 * kk, dsc(iprev + kk * 64, DH32A));
            wg_commit();
            wg_wait<0>();
            fence_regs<8>(agg);
            flush(tt.x, true);
            if (Tu > 1) {
                const int sl = (tt.x >> 6) & 15;
                const bool mine = q == ((sl & 7) >> 1);
                const uint32_t xa = sb + SM_XB + hu * 256 + (warp4 * 8 + (lane >> 2)) * 8;
                const float v0 = (sl & 8) ? ((sl & 1) ? agg[5] : agg[4]) : ((sl & 1) ? agg[1] : agg[0]);
                const float v1 = (sl & 8) ? ((sl & 1) ? agg[7] : agg[6]) : ((sl & 1) ? agg[3] : agg[2]);
                if (su) {
                    if (mine) sts64(xa, __float_as_uint(v0), __float_as_uint(v1));
                    if (hu) bar_arrive<8, 256>(); else bar_arrive<7, 256>();
                } else {
                    if (hu) bar_sync<8, 256>(); else bar_sync<7, 256>();
                    const uint32_t ra = (sl & 8) ? ((sl & 1) ? fa[3] : fa[2]) + 12288 : ((sl & 1) ? fa[1] : fa[0]);
                    if (mine) sts32(ra, pack2(v0 + __uint_as_float(lds32(xa)), v1 + __uint_as_float(lds32(xa + 4))));
                }
            }
        }
    }
    CSTAMP(10, tid == 0);
    fence_async();
    bar_sync<1, NT>();
    if (wg < 3) tail_gemm<1>(sb, wg, warp4, lane, cta, a.out);
    else tail_scan(sb, tid - 384);
    CSTAMP(15, tid == 0);
    if (!tail_failed(sb) || T == 0) return false;
    asm volatile("setmaxnreg.dec.sync.aligned.u32 96;");
    return true;
}

template <int MODE>
__global__ void __launch_bounds__(NT, 1) mpnn_kernel(const __grid_constant__ Args a) {
    extern __shared__ __align__(1024) uint8_t smem[];
    const uint32_t sb = (uint32_t)__cvta_generic_to_shared(smem);
    TSTAMP(0, threadIdx.x == 0);
    CSTAMP(1, threadIdx.x == 0);
    const bool slow = threadIdx.x >= 512 ? producer<MODE>(sb, a) : consumer<MODE>(sb, a);
    if ((MODE & 2) && slow) slow_path(sb, blockIdx.x, a);
    CSTAMP(11, threadIdx.x == 0);
    TSTAMP(12, threadIdx.x == 0);
}

}

extern "C" void kernel_launch(void* const* d_in, const int* in_sizes, int n_in, void* d_out, int out_size) {
    (void)in_sizes; (void)n_in; (void)out_size;
    static int fused = -1;
    static void *p_ra, *p_rx, *p_xh, *p_ctl;
    if (fused < 0) {
        cudaGetSymbolAddress(&p_ra, g_ra);
        cudaGetSymbolAddress(&p_rx, g_rx);
        cudaGetSymbolAddress(&p_xh, g_xh);
        cudaGetSymbolAddress(&p_ctl, g_ctl);
        int dev = 0, sms = 0, nb = 0;
        cudaGetDevice(&dev);
        cudaDeviceGetAttribute(&sms, cudaDevAttrMultiProcessorCount, dev);
        cudaFuncSetAttribute(mpnn_kernel<1>, cudaFuncAttributeMaxDynamicSharedMemorySize, SM_TOTAL);
        cudaFuncSetAttribute(mpnn_kernel<2>, cudaFuncAttributeMaxDynamicSharedMemorySize, SM_TOTAL);
        cudaFuncSetAttribute(mpnn_kernel<3>, cudaFuncAttributeMaxDynamicSharedMemorySize, SM_TOTAL);
        cudaOccupancyMaxActiveBlocksPerMultiprocessor(&nb, mpnn_kernel<3>, NT, SM_TOTAL);
        fused = (sms * nb >= G) ? 1 : 0;
    }
    Args a;
    a.x   = (const __nv_bfloat16*)d_in[0];
    a.ea  = (const __nv_bfloat16*)d_in[1];
    a.src = (const int*)d_in[2];
    a.dst = (const int*)d_in[3];
    a.w1  = (const __nv_bfloat16*)d_in[4];
    a.b1  = (const __nv_bfloat16*)d_in[5];
    a.w2  = (const __nv_bfloat16*)d_in[6];
    a.b2  = (const __nv_bfloat16*)d_in[7];
    a.out = (__nv_bfloat16*)d_out;
    a.ra  = (uint4*)p_ra;
    a.rx  = (uint2*)p_rx;
    a.xh  = (uint4*)p_xh;
    a.ctl = (uint32_t*)p_ctl;
    cudaStream_t s = cudaStreamPerThread;
    if (fused) {
        mpnn_kernel<3><<<G, NT, SM_TOTAL, s>>>(a);
    } else {
        mpnn_kernel<1><<<G, NT, SM_TOTAL, s>>>(a);
        mpnn_kernel<2><<<G, NT, SM_TOTAL, s>>>(a);
    }
}
```

```cpp
#include <cuda_runtime.h>
#include <cuda_bf16.h>
#include <stdint.h>

#define RELX 0
#define PUBR -1
#define PDT 220
#define PROWS 16
#define XAT 0
namespace {

constexpr int NN   = 25000;
constexpr int NE   = 800000;
constexpr int G    = 132;
constexpr int NPB  = 190;
constexpr int CH   = 6064;
constexpr int CAPT = 52;
constexpr int CAP  = CAPT * 128;
constexpr int NT   = 640;
constexpr int CAPB = 48;
constexpr int OVC  = 64;
constexpr int BINP = CAPB * 4 + 4;
constexpr int RP   = 304;
constexpr int RS   = RP / 4 - 1, RU = RP / 16, RX = 32;
constexpr uint32_t CINC = (1u << 18) + 4u;
constexpr uint32_t RUNL = (uint32_t)RS << 18, BINL = (uint32_t)(CAPB + 1) << 18;
constexpr uint32_t TAGM = 511u << 13, PADW = 0x800000u;

constexpr int SM_CNT  = 0;
constexpr int SM_DEG  = 576;
constexpr int SM_FLAG = SM_DEG + 896;
constexpr int SM_TT   = SM_FLAG + 32;
constexpr int SM_XB   = SM_TT + 1024;
constexpr int SM_B1   = SM_XB + 512;
constexpr int SM_B2   = SM_B1 + 256;
constexpr int SM_BAR  = SM_B2 + 128;
constexpr int SM_XE   = 5120;
constexpr int XE_S    = 20480, XE_P = 65536;
constexpr int SM_IND  = SM_XE + 2 * XE_S;
constexpr int SM_POS  = SM_XE + XE_P + 2 * XE_S;
constexpr int SM_RAW  = 126976;
constexpr int SM_QA   = SM_RAW + 16384;
constexpr int SM_BIN  = SM_QA + 49152;
constexpr int SM_OVL  = SM_BIN + NPB * BINP;
constexpr int SM_SR   = SM_OVL + OVC * 8 + 8;
constexpr int SM_TOTAL = SM_SR + 2048;
constexpr uint32_t OVLO = SM_OVL - SM_BIN, PADO = OVLO + OVC * 8;
constexpr int F_TOT = SM_FLAG, F_DMAX = SM_FLAG + 4, F_BAD = SM_FLAG + 8, F_WMAX = SM_FLAG + 12, F_NF = SM_FLAG + 16,
              F_BIG = SM_FLAG + 20, F_XC = SM_FLAG + 28;
constexpr int SM_STA  = SM_XE;
constexpr int SM_XO   = SM_IND;
constexpr int SM_XR   = SM_XE + XE_P;
constexpr int SM_W1B  = SM_XR + 24576;
constexpr int SM_W1A  = SM_POS;
constexpr int B_X = SM_BAR + 64;
constexpr int SM_W2   = SM_BIN;
constexpr int SM_SAGG = SM_XE;
constexpr int SM_SQ   = SM_SAGG + NPB * 512;
static_assert(B_X + 8 <= SM_XE && SM_IND + 24576 == SM_XE + XE_P && SM_POS + CAP * 2 <= SM_RAW && SM_STA + G * RP <= SM_IND, "map");
static_assert(SM_W1B + 16384 <= SM_POS && SM_W1A + 20480 <= SM_QA, "map");
static_assert(SM_SQ <= SM_QA && SM_SQ + NPB * 512 <= SM_TOTAL && SM_TOTAL <= 232448 && PADO < 65536, "map");
static_assert(G * (RS + RX) + 2 < 16384 && G * RU <= 5 * 512 && G * CH >= NE && NE - (G - 1) * CH > 4096 && CH <= 6144 && CH % 4 == 0, "fields");
static_assert(SM_W2 % 1024 == 0 && SM_QA % 1024 == 0 && SM_XO % 1024 == 0 && SM_W1A % 1024 == 0 && SM_W1B % 1024 == 0 &&
              SM_B1 % 16 == 0 && SM_TT % 16 == 0 && SM_BAR % 8 == 0 && SM_STA % 16 == 0 && SM_OVL % 8 == 0 && SM_XR % 16 == 0 && SM_SR % 16 == 0 && SM_DEG % 16 == 0, "align");

__device__ uint4 g_ra[G * G * RU];
__device__ uint2 g_rx[G * G * RX];
__device__ uint4 g_xh[(NN + 1) * 8];
__device__ uint32_t g_ctl[(G + 1) * 32];
#define TSTAMP(i, cond)
#define CSTAMP(i, cond)

__device__ __forceinline__ uint64_t mkdesc(uint32_t addr, uint32_t lbo, uint32_t sbo, uint32_t swz) {
    return (uint64_t)((addr & 0x3FFFF) >> 4) | ((uint64_t)(lbo >> 4) << 16) | ((uint64_t)(sbo >> 4) << 32) |
           ((uint64_t)swz << 62);
}
__device__ __forceinline__ void wg_fence()  { asm volatile("wgmma.fence.sync.aligned;" ::: "memory"); }
__device__ __forceinline__ void wg_commit() { asm volatile("wgmma.commit_group.sync.aligned;" ::: "memory"); }
template <int N> __device__ __forceinline__ void wg_wait() { asm volatile("wgmma.wait_group.sync.aligned %0;" ::"n"(N) : "memory"); }
__device__ __forceinline__ void fence_async() { asm volatile("fence.proxy.async.shared::cta;" ::: "memory"); }

#define R8(d, o) "+f"(d[o + 0]), "+f"(d[o + 1]), "+f"(d[o + 2]), "+f"(d[o + 3]), "+f"(d[o + 4]), "+f"(d[o + 5]), "+f"(d[o + 6]), "+f"(d[o + 7])
#define W8(d, o) "=f"(d[o + 0]), "=f"(d[o + 1]), "=f"(d[o + 2]), "=f"(d[o + 3]), "=f"(d[o + 4]), "=f"(d[o + 5]), "=f"(d[o + 6]), "=f"(d[o + 7])
#define U8(d, o) "+r"(d[o + 0]), "+r"(d[o + 1]), "+r"(d[o + 2]), "+r"(d[o + 3]), "+r"(d[o + 4]), "+r"(d[o + 5]), "+r"(d[o + 6]), "+r"(d[o + 7])
#define V8(d, o) "=r"(d[o + 0]), "=r"(d[o + 1]), "=r"(d[o + 2]), "=r"(d[o + 3]), "=r"(d[o + 4]), "=r"(d[o + 5]), "=r"(d[o + 6]), "=r"(d[o + 7])
#define L32 "{%0,%1,%2,%3,%4,%5,%6,%7,%8,%9,%10,%11,%12,%13,%14,%15,%16,%17,%18,%19,%20,%21,%22,%23,%24,%25,%26,%27,%28,%29,%30,%31}"
#define L48 "{%0,%1,%2,%3,%4,%5,%6,%7,%8,%9,%10,%11,%12,%13,%14,%15,%16,%17,%18,%19,%20,%21,%22,%23,%24,%25,%26,%27,%28,%29,%30,%31,%32,%33,%34,%35,%36,%37,%38,%39,%40,%41,%42,%43,%44,%45,%46,%47}"

__device__ __forceinline__ void h128z(uint32_t* d, const uint32_t* a, uint64_t db) {
    asm volatile("{.reg .pred p; setp.ne.b32 p, 0, 0;\n"
                 "wgmma.mma_async.sync.aligned.m64n128k16.f16.f16.f16 " L32 ", {%32,%33,%34,%35}, %36, p, 1, 1, 0;}"
                 : V8(d, 0), V8(d, 8), V8(d, 16), V8(d, 24) : "r"(a[0]), "r"(a[1]), "r"(a[2]), "r"(a[3]), "l"(db));
}
__device__ __forceinline__ void h128(uint32_t* d, const uint32_t* a, uint64_t db) {
    asm volatile("{.reg .pred p; setp.eq.b32 p, 0, 0;\n"
                 "wgmma.mma_async.sync.aligned.m64n128k16.f16.f16.f16 " L32 ", {%32,%33,%34,%35}, %36, p, 1, 1, 0;}"
                 : U8(d, 0), U8(d, 8), U8(d, 16), U8(d, 24) : "r"(a[0]), "r"(a[1]), "r"(a[2]), "r"(a[3]), "l"(db));
}
__device__ __forceinline__ void h128s(uint32_t* d, uint64_t da, uint64_t db) {
    asm volatile("{.reg .pred p; setp.eq.b32 p, 0, 0;\n"
                 "wgmma.mma_async.sync.aligned.m64n128k16.f16.f16.f16 " L32 ", %32, %33, p, 1, 1, 1, 0;}"
                 : U8(d, 0), U8(d, 8), U8(d, 16), U8(d, 24) : "l"(da), "l"(db));
}
__device__ __forceinline__ void r16t(float* d, const uint32_t* a, uint64_t db) {
    asm volatile("{.reg .pred p; setp.eq.b32 p, 0, 0;\n"
                 "wgmma.mma_async.sync.aligned.m64n16k16.f32.f16.f16 {%0,%1,%2,%3,%4,%5,%6,%7}, {%8,%9,%10,%11}, %12, p, 1, 1, 1;}"
                 : R8(d, 0) : "r"(a[0]), "r"(a[1]), "r"(a[2]), "r"(a[3]), "l"(db));
}
__device__ __forceinline__ void q_gemm(float* d, uint64_t da, uint64_t db) {
    asm volatile("{.reg .pred p, q; .reg .b64 a, b; setp.ne.b32 p, 0, 0; setp.eq.b32 q, 0, 0;\n"
                 "wgmma.fence.sync.aligned;\n"
                 "wgmma.mma_async.sync.aligned.m64n96k16.f32.bf16.bf16 " L48 ", %48, %49, p, 1, 1, 1, 0;\n"
                 "add.s64 a, %48, 128; add.s64 b, %49, 2;\n"
                 "wgmma.mma_async.sync.aligned.m64n96k16.f32.bf16.bf16 " L48 ", a, b, q, 1, 1, 1, 0;\n"
                 "add.s64 a, %48, 256; add.s64 b, %49, 4;\n"
                 "wgmma.mma_async.sync.aligned.m64n96k16.f32.bf16.bf16 " L48 ", a, b, q, 1, 1, 1, 0;\n"
                 "add.s64 a, %48, 384; add.s64 b, %49, 6;\n"
                 "wgmma.mma_async.sync.aligned.m64n96k16.f32.bf16.bf16 " L48 ", a, b, q, 1, 1, 1, 0;\n"
                 "wgmma.commit_group.sync.aligned;\n"
                 "wgmma.wait_group.sync.aligned 0;}"
                 : W8(d, 0), W8(d, 8), W8(d, 16), W8(d, 24), W8(d, 32), W8(d, 40)
                 : "l"(da), "l"(db) : "memory");
}
__device__ __forceinline__ void ss64t(float* d, uint64_t da, uint64_t db, int acc) {
    asm volatile("{.reg .pred p; setp.ne.b32 p, %34, 0;\n"
                 "wgmma.mma_async.sync.aligned.m64n64k16.f32.bf16.bf16 " L32 ", %32, %33, p, 1, 1, 0, 1;}"
                 : R8(d, 0), R8(d, 8), R8(d, 16), R8(d, 24)
                 : "l"(da), "l"(db), "r"(acc));
}
template <int NREG> __device__ __forceinline__ void fence_regs(float* d) {
#pragma unroll
    for (int i = 0; i < NREG; i++) asm volatile("" : "+f"(d[i])::"memory");
}
template <int NREG> __device__ __forceinline__ void fence_regs(uint32_t* d) {
#pragma unroll
    for (int i = 0; i < NREG; i++) asm volatile("" : "+r"(d[i])::"memory");
}
__device__ __forceinline__ void ldsm4t(uint32_t* r, uint32_t addr) {
    asm volatile("ldmatrix.sync.aligned.m8n8.x4.trans.shared.b16 {%0,%1,%2,%3}, [%4];"
                 : "=r"(r[0]), "=r"(r[1]), "=r"(r[2]), "=r"(r[3]) : "r"(addr) : "memory");
}
__device__ __forceinline__ void stsm4t(uint32_t addr, uint32_t a, uint32_t b, uint32_t c, uint32_t d) {
    asm volatile("stmatrix.sync.aligned.m8n8.x4.trans.shared.b16 [%0], {%1,%2,%3,%4};" ::"r"(addr), "r"(a), "r"(b), "r"(c), "r"(d) : "memory");
}
__device__ __forceinline__ void cp16(uint32_t s, const void* g) {
    asm volatile("cp.async.cg.shared.global [%0], [%1], 16;" ::"r"(s), "l"(g) : "memory");
}
__device__ __forceinline__ void cp4(uint32_t s, const void* g) {
    asm volatile("cp.async.ca.shared.global [%0], [%1], 4;" ::"r"(s), "l"(g) : "memory");
}
__device__ __forceinline__ void cp16z(uint32_t s, const void* g, uint32_t skip) {
    asm volatile("{.reg .pred p; setp.ne.u32 p, %2, 0; cp.async.cg.shared.global [%0], [%1], 16, p;}" ::"r"(s), "l"(g), "r"(skip) : "memory");
}
__device__ __forceinline__ void cp_commit() { asm volatile("cp.async.commit_group;" ::: "memory"); }
template <int N> __device__ __forceinline__ void cp_wait() { asm volatile("cp.async.wait_group %0;" ::"n"(N) : "memory"); }
__device__ __forceinline__ void cp_wait_all() { asm volatile("cp.async.wait_all;" ::: "memory"); }
__device__ __forceinline__ void mbar_init(uint32_t a, int cnt) { asm volatile("mbarrier.init.shared::cta.b64 [%0], %1;" ::"r"(a), "r"(cnt) : "memory"); }
__device__ __forceinline__ void mbar_arrive(uint32_t a) { asm volatile("mbarrier.arrive.shared::cta.b64 _, [%0];" ::"r"(a) : "memory"); }
__device__ __forceinline__ void mbar_cp_arrive(uint32_t a) { asm volatile("cp.async.mbarrier.arrive.noinc.shared::cta.b64 [%0];" ::"r"(a) : "memory"); }
__device__ __forceinline__ void mbar_wait(uint32_t a, uint32_t parity) {
    asm volatile("{.reg .pred p; .reg .u32 n; mov.u32 n, 0;\n"
                 "MW_%=: mbarrier.try_wait.parity.shared::cta.b64 p, [%0], %1;\n"
                 "@p bra MD_%=;\n"
                 "add.u32 n, n, 1; setp.gt.u32 p, n, 0x100000;\n"
                 "@p trap;\n"
                 "bra MW_%=;\n"
                 "MD_%=: }" ::"r"(a), "r"(parity) : "memory");
}
template <int ID, int CNT> __device__ __forceinline__ void bar_sync()   { asm volatile("bar.sync %0, %1;" ::"n"(ID), "n"(CNT) : "memory"); }
template <int ID, int CNT> __device__ __forceinline__ void bar_arrive() { asm volatile("bar.arrive %0, %1;" ::"n"(ID), "n"(CNT) : "memory"); }
__device__ __forceinline__ float tanh_fast(float x) { float y; asm("tanh.approx.f32 %0, %1;" : "=f"(y) : "f"(x)); return y; }
__device__ __forceinline__ uint32_t pack2(float lo, float hi) {
    uint32_t r; asm("cvt.rn.bf16x2.f32 %0, %1, %2;" : "=r"(r) : "f"(hi), "f"(lo)); return r;
}
__device__ __forceinline__ uint32_t pack2h(float lo, float hi) {
    uint32_t r; asm("cvt.rn.f16x2.f32 %0, %1, %2;" : "=r"(r) : "f"(hi), "f"(lo)); return r;
}
__device__ __forceinline__ float bf_lo(uint32_t v) { return __uint_as_float(v << 16); }
__device__ __forceinline__ float bf_hi(uint32_t v) { return __uint_as_float(v & 0xFFFF0000u); }
__device__ __forceinline__ uint32_t bf2h(uint32_t v) { return pack2h(bf_lo(v), bf_hi(v)); }
__device__ __forceinline__ uint32_t amax2(uint32_t a, uint32_t b) {
    uint32_t r; asm("max.NaN.xorsign.abs.bf16x2 %0, %1, %2;" : "=r"(r) : "r"(a), "r"(b)); return r;
}
__device__ __forceinline__ uint32_t amax_fin(uint32_t m) { return max(m & 0x7FFFu, (m >> 16) & 0x7FFFu); }
__device__ __forceinline__ uint32_t silu_h2(uint32_t h) {
    uint32_t t, s;
    asm("tanh.approx.f16x2 %0, %1;" : "=r"(t) : "r"(h));
    asm("fma.rn.f16x2 %0, %1, %2, %1;" : "=r"(s) : "r"(h), "r"(t));
    return s;
}
__device__ __forceinline__ uint32_t hadd2(uint32_t a, uint32_t b) { uint32_t s; asm("add.rn.f16x2 %0, %1, %2;" : "=r"(s) : "r"(a), "r"(b)); return s; }
__device__ __forceinline__ uint32_t lds32(uint32_t a) { uint32_t v; asm volatile("ld.shared.b32 %0, [%1];" : "=r"(v) : "r"(a) : "memory"); return v; }
__device__ __forceinline__ uint32_t lds16(uint32_t a) { uint32_t v; asm volatile("ld.shared.u16 %0, [%1];" : "=r"(v) : "r"(a) : "memory"); return v; }
__device__ __forceinline__ uint4 lds128(uint32_t a) {
    uint4 v; asm volatile("ld.shared.v4.b32 {%0,%1,%2,%3}, [%4];" : "=r"(v.x), "=r"(v.y), "=r"(v.z), "=r"(v.w) : "r"(a) : "memory"); return v;
}
__device__ __forceinline__ void sts16(uint32_t a, uint32_t v) { asm volatile("st.shared.u16 [%0], %1;" ::"r"(a), "r"(v) : "memory"); }
__device__ __forceinline__ void sts32(uint32_t a, uint32_t v) { asm volatile("st.shared.b32 [%0], %1;" ::"r"(a), "r"(v) : "memory"); }
__device__ __forceinline__ void sts64(uint32_t a, uint32_t x, uint32_t y) { asm volatile("st.shared.v2.b32 [%0], {%1,%2};" ::"r"(a), "r"(x), "r"(y) : "memory"); }
__device__ __forceinline__ void sts128(uint32_t a, uint32_t x, uint32_t y, uint32_t z, uint32_t w) {
    asm volatile("st.shared.v4.b32 [%0], {%1,%2,%3,%4};" ::"r"(a), "r"(x), "r"(y), "r"(z), "r"(w) : "memory");
}
template <uint32_t V> __device__ __forceinline__ uint32_t atoms_add(uint32_t a) {
    uint32_t v; asm volatile("atom.shared.add.u32 %0, [%1], %2;" : "=r"(v) : "r"(a), "n"(V) : "memory"); return v;
}
__device__ __forceinline__ uint2 lds64(uint32_t a) {
    uint2 v; asm volatile("ld.shared.v2.b32 {%0,%1}, [%2];" : "=r"(v.x), "=r"(v.y) : "r"(a) : "memory"); return v;
}
__device__ __forceinline__ void st_rel64(void* p, uint32_t x, uint32_t y) {
    asm volatile("st.relaxed.gpu.global.b64 [%0], %1;" ::"l"(p), "l"((uint64_t)x | ((uint64_t)y << 32)) : "memory");
}
__device__ __forceinline__ uint64_t ld_rel64(const void* p) {
    uint64_t v; asm volatile("ld.relaxed.gpu.global.b64 %0, [%1];" : "=l"(v) : "l"(p) : "memory"); return v;
}
__device__ __forceinline__ uint32_t ld_acq32(const void* p) {
    uint32_t v; asm volatile("ld.acquire.gpu.global.b32 %0, [%1];" : "=r"(v) : "l"(p) : "memory"); return v;
}
__device__ __forceinline__ uint32_t ld_g32(const void* p) {
    uint32_t v; asm volatile("ld.global.b32 %0, [%1];" : "=r"(v) : "l"(p) : "memory"); return v;
}
__device__ __forceinline__ uint32_t ld_src(const void* p, uint32_t rec) {
    uint32_t v;
    asm volatile("{.reg .pred q; .reg .u64 a; .reg .u32 t; and.b32 t, %2, %3; setp.eq.u32 q, t, 0; and.b32 t, %2, 0xFFFFF; mad.wide.u32 a, t, 4, %1;\n"
                 "mov.b32 %0, %4; @q ld.global.nc.L1::no_allocate.b32 %0, [a];}" : "=&r"(v) : "l"(p), "r"(rec), "n"(PADW), "n"(NN) : "memory");
    return v;
}
__device__ __forceinline__ uint4 ld_row(const void* p, uint32_t n) {
    uint4 v;
    asm volatile("{.reg .pred q; .reg .u64 a; setp.lt.u32 q, %5, %6; mad.wide.u32 a, %5, 128, %4;\n"
                 "mov.b32 %0, 0; mov.b32 %1, 0; mov.b32 %2, 0; mov.b32 %3, 0;\n"
                 "@q ld.global.L1::no_allocate.v4.b32 {%0,%1,%2,%3}, [a];}"
                 : "=&r"(v.x), "=&r"(v.y), "=&r"(v.z), "=&r"(v.w) : "l"(p), "r"(n), "n"(NN) : "memory");
    return v;
}
__device__ __forceinline__ uint4 ld_stream(const void* p) {
    uint4 v;
    asm volatile("ld.global.nc.L1::no_allocate.v4.b32 {%0,%1,%2,%3}, [%4];" : "=r"(v.x), "=r"(v.y), "=r"(v.z), "=r"(v.w) : "l"(p) : "memory");
    return v;
}
__device__ __forceinline__ uint32_t atoms_addr(uint32_t a, uint32_t inc) {
    uint32_t v; asm volatile("atom.shared.add.u32 %0, [%1], %2;" : "=r"(v) : "r"(a), "r"(inc) : "memory"); return v;
}
template <uint32_t LIM, uint32_t BIT> __device__ __forceinline__ void put(uint32_t v, uint32_t w, uint32_t& mask) {
    asm volatile("{.reg .pred q, o; .reg .u32 t; setp.lt.u32 q|o, %1, %3; and.b32 t, %1, 0x3FFFF;\n"
                 "@q st.shared.b32 [t], %2; @o or.b32 %0, %0, %4;}" : "+r"(mask) : "r"(v), "r"(w), "n"(LIM), "n"(BIT) : "memory");
}
template <uint32_t LIM> __device__ __forceinline__ void put(uint32_t v, uint32_t w) {
    asm volatile("{.reg .pred q; .reg .u32 t; setp.lt.u32 q, %0, %2; and.b32 t, %0, 0x3FFFF; @q st.shared.b32 [t], %1;}"
                 ::"r"(v), "r"(w), "n"(LIM) : "memory");
}
__device__ __forceinline__ uint4 ld_rec(const uint4* p) {
    uint4 v;
    asm volatile("ld.relaxed.gpu.global.v4.b32 {%0,%1,%2,%3}, [%4];" : "=r"(v.x), "=r"(v.y), "=r"(v.z), "=r"(v.w) : "l"(p) : "memory");
    return v;
}
__device__ __forceinline__ void bulk_store(void* g, uint32_t s, uint32_t bytes) {
    asm volatile("cp.async.bulk.global.shared::cta.bulk_group [%0], [%1], %2;\n"
                 "cp.async.bulk.commit_group;" ::"l"(g), "r"(s), "r"(bytes) : "memory");
}
__device__ __forceinline__ void bulk_wait()      { asm volatile("cp.async.bulk.wait_group 0;" ::: "memory"); }
__device__ __forceinline__ void bulk_wait_read() { asm volatile("cp.async.bulk.wait_group.read 0;" ::: "memory"); }
__device__ __forceinline__ void l2_prefetch(const void* p, uint32_t bytes) {
    asm volatile("cp.async.bulk.prefetch.L2.global [%0], %1;" ::"l"(p), "r"(bytes) : "memory");
}
__device__ __forceinline__ const char* madw(uint32_t a, uint32_t b, const char* p) {
    const char* r; asm("mad.wide.u32 %0, %1, %2, %3;" : "=l"(r) : "r"(a), "r"(b), "l"(p)); return r;
}
__device__ __forceinline__ uint64_t dsc(uint32_t lo, uint32_t hi) { return (uint64_t)lo | ((uint64_t)hi << 32); }
__device__ __forceinline__ uint32_t dlo(uint32_t addr) { return ((addr & 0x3FFFF) >> 4) | 0x10000u; }
constexpr uint32_t DH128 = (1024 >> 4) | (1u << 30), DH32A = (512 >> 4) | (3u << 30), DH32B = (256 >> 4) | (3u << 30);
__device__ __forceinline__ bool elect() {
    uint32_t r;
    asm volatile("{.reg .pred p; elect.sync _|p, 0xFFFFFFFF; selp.u32 %0, 1, 0, p;}" : "=r"(r));
    return r != 0;
}
__device__ __forceinline__ int node2row(int n) { return ((n >> 3) & 1) * 96 + (n >> 4) * 8 + (n & 7); }
__device__ __forceinline__ int row2node(int r) { return r < 96 ? (r >> 3) * 16 + (r & 7) : ((r - 96) >> 3) * 16 + 8 + (r & 7); }
__device__ __forceinline__ int col2pos(int c) { return (c & ~15) | ((c & 7) << 1) | ((c >> 3) & 1); }

struct Args {
    uint32_t* ctl;
    const int* dst;
    uint4* ra;
    const __nv_bfloat16 *x, *w1, *b1;
    const int* src;
    const __nv_bfloat16 *ea, *w2, *b2;
    __nv_bfloat16* out;
    uint4* xh;
    uint2* rx;
};

__device__ __forceinline__ void bin_overflow(uint32_t sb, uint32_t rec, uint32_t v) {
    const uint32_t ix = atoms_add<1>(sb + F_XC);
    if (ix < OVC) sts64(sb + SM_OVL + ix * 8, rec, v);
    else sts32(sb + F_BAD, 1u);
}
__device__ __forceinline__ void send_extra(uint32_t sb, uint32_t mask, uint32_t ep, const Args& a) {
#pragma unroll 1
    while (mask) {
        const uint32_t i = __ffs(mask) - 1, off = threadIdx.x * 4 + (3 - (i >> 2)) * 2048 + (i & 3);
        mask &= mask - 1;
        const uint32_t d = a.dst[blockIdx.x * CH + off], b = __umulhi(d, 22605092u);
        const uint32_t ix = atoms_add<1>(sb + SM_STA + (b + (b < blockIdx.x ? G : 0) - blockIdx.x) * RP + RS * 4) & 0x1FFFu;
        if (ix < RX) st_rel64(a.rx + (b * G + blockIdx.x) * RX + ix, ((d - b * NPB) << 24) + off, ep);
    }
}
template <int MODE> __device__ __forceinline__ void recv_extra(uint32_t sb, uint32_t n, uint32_t run, uint32_t ep, const Args& a) {
    if (n > RX) { sts32(sb + F_BAD, 1u); n = 0; }
    const uint2* p = a.rx + (blockIdx.x * G + run) * RX;
#pragma unroll 1
    for (uint32_t i = 0; i < n; i++) {
        uint64_t w = ld_rel64(p + i);
        int it = 0;
        while (MODE == 3 && (uint32_t)(w >> 32) != ep) {
            if (++it > (1 << 22)) __trap();
            w = ld_rel64(p + i);
        }
        const uint32_t rec = (uint32_t)w + run * CH, v = atoms_add<CINC>(sb + SM_DEG + (rec >> 24) * 4);
        if (v < BINL) sts32(v & 0x3FFFFu, rec);
        else bin_overflow(sb, rec, v);
    }
}
__device__ __forceinline__ void load_w2(uint32_t sb, int u, int nthr, const Args& a) {
    for (int i = u; i < 128 * 32; i += nthr) {
        const int kp = i >> 5, w = i & 31;
        const int k = (kp & ~15) | ((kp & 1) << 3) | ((kp >> 1) & 7);
        cp4(sb + SM_W2 + kp * 128 + (((w & 7) ^ (kp & 7)) << 4) + (w >> 3) * 4, a.w2 + k * 64 + w * 2);
    }
    if (u < 8) cp16(sb + SM_B2 + u * 16, a.b2 + u * 8);
    cp_wait_all();
}

template <int FAST> __device__ __forceinline__ void tail_gemm(uint32_t sb, int wg, int warp4, int lane, int bucket, __nv_bfloat16* __restrict__ out) {
    const int g = lane >> 2, q = lane & 3;
    float d[32];
#pragma unroll
    for (int i = 0; i < 32; i++) d[i] = 0.f;
    wg_fence();
#pragma unroll
    for (int ks = 0; ks < 8; ks++)
        ss64t(d, mkdesc(sb + SM_QA + (ks >> 2) * 24576 + wg * 8192 + (ks & 3) * 32, 16, 1024, 1),
              mkdesc(sb + SM_W2 + ks * 2048, 16, 1024, 1), ks);
    wg_commit();
    const uint4 bb0 = lds128(sb + SM_B2 + q * 32), bb1 = lds128(sb + SM_B2 + q * 32 + 16);
    const int node0 = row2node(wg * 64 + warp4 * 16 + g);
    const uint32_t dg0 = (lds32(sb + SM_DEG + node0 * 4) >> (18 * FAST)) - FAST, dg1 = (lds32(sb + SM_DEG + node0 * 4 + 64) >> (18 * FAST)) - FAST;
    wg_wait<0>();
    fence_regs<32>(d);
    const uint32_t bw[8] = {bb0.x, bb0.y, bb0.z, bb0.w, bb1.x, bb1.y, bb1.z, bb1.w};
    uint32_t m = 0;
#pragma unroll
    for (int r = 0; r < 2; r++) {
        const int node = node0 + 16 * r;
        const int gn = bucket * NPB + node;
        const uint32_t dg = r ? dg1 : dg0;
        const float fd = (float)dg;
        uint32_t o[8];
#pragma unroll
        for (int j = 0; j < 8; j++) {
            const float v0 = fmaf(fd, bf_lo(bw[j]), d[4 * j + 2 * r]);
            const float v1 = fmaf(fd, bf_hi(bw[j]), d[4 * j + 2 * r + 1]);
            o[j] = dg ? pack2(v0, v1) : 0u;
            m = amax2(m, o[j]);
        }
        if (node < NPB && gn < NN) {
            uint4* op = reinterpret_cast<uint4*>(out + (size_t)gn * 64 + 16 * q);
            op[0] = make_uint4(o[0], o[1], o[2], o[3]);
            op[1] = make_uint4(o[4], o[5], o[6], o[7]);
        }
    }
    if (amax_fin(m) >= 0x7F80u) sts32(sb + F_NF, 1u);
}
__device__ __forceinline__ void tail_scan(uint32_t sb, int u) {
    uint32_t m = 0;
#pragma unroll
    for (int j = 0; j < 6; j++) {
        const int row = (u >> 3) + 32 * j;
        const uint32_t dg = lds32(sb + SM_DEG + row2node(row) * 4) >> 19;
        const uint4 a = lds128(sb + SM_QA + row * 128 + (u & 7) * 16), b = lds128(sb + SM_QA + 24576 + row * 128 + (u & 7) * 16);
        const uint32_t v = amax2(amax2(amax2(a.x, a.y), amax2(a.z, a.w)), amax2(amax2(b.x, b.y), amax2(b.z, b.w)));
        if (dg) m = amax2(m, v);
    }
    const float thr = (float)lds32(sb + F_DMAX) * (1.f / 32768.f) * fmaf(88.f, bf_lo(lds32(sb + F_WMAX)), 30.f);
    if (bf_lo(amax_fin(m)) >= thr) sts32(sb + F_BIG, 1u);
}
__device__ __forceinline__ bool tail_failed(uint32_t sb) {
    bar_sync<1, NT>();
    return lds32(sb + F_NF) != 0 || lds32(sb + F_BIG) == 0;
}

__device__ __forceinline__ void slow_path(uint32_t sb, int bucket, const Args& a) {
    const int tid = threadIdx.x, lane = tid & 31, j = tid & 127, wg = tid >> 7;
    bar_sync<0, NT>();
    for (int i = tid; i < NPB * 128; i += NT) sts32(sb + SM_SAGG + i * 4, 0u);
    if (tid < 192) sts32(sb + SM_DEG + tid * 4, 0u);
    const unsigned short* w1u = reinterpret_cast<const unsigned short*>(a.w1);
    {
        uint32_t w[32];
#pragma unroll
        for (int k = 0; k < 32; k++) w[k] = w1u[(64 + 2 * k) * 128 + j] | ((uint32_t)w1u[(65 + 2 * k) * 128 + j] << 16);
        const float bj = __bfloat162float(a.b1[j]);
        for (int node = wg; node < NPB && bucket * NPB + node < NN; node += 5) {
            const uint4* xr = reinterpret_cast<const uint4*>(a.x + (size_t)(bucket * NPB + node) * 64);
            float h = bj;
            fence_regs<32>(w);
#pragma unroll
            for (int k = 0; k < 8; k++) {
                const uint4 v = __ldg(xr + k);
                const uint32_t vv[4] = {v.x, v.y, v.z, v.w};
#pragma unroll
                for (int i = 0; i < 4; i++) {
                    h = fmaf(bf_lo(vv[i]), bf_lo(w[4 * k + i]), h);
                    h = fmaf(bf_hi(vv[i]), bf_hi(w[4 * k + i]), h);
                }
            }
            sts32(sb + SM_SQ + (node * 128 + j) * 4, __float_as_uint(h));
        }
    }
    uint32_t w[40];
#pragma unroll
    for (int k = 0; k < 40; k++) {
        const int r = k < 32 ? 2 * k : 2 * k + 64;
        w[k] = w1u[r * 128 + j] | ((uint32_t)w1u[(r + 1) * 128 + j] << 16);
    }
    bar_sync<0, NT>();
    for (int e0 = wg * 32; e0 < NE; e0 += 160) {
        const int dn = a.dst[e0 + lane] - bucket * NPB;
        unsigned m = __ballot_sync(0xFFFFFFFFu, dn >= 0 && dn < NPB);
        while (m) {
            const int l = __ffs(m) - 1;
            m &= m - 1;
            const int node = __shfl_sync(0xFFFFFFFFu, dn, l);
            const int e = e0 + l;
            const uint4* xr = reinterpret_cast<const uint4*>(a.x + (size_t)a.src[e] * 64);
            const uint4* er = reinterpret_cast<const uint4*>(a.ea + (size_t)e * 16);
            float h = __uint_as_float(lds32(sb + SM_SQ + (node * 128 + j) * 4));
            fence_regs<40>(w);
#pragma unroll
            for (int k = 0; k < 10; k++) {
                const uint4 v = (k < 8) ? __ldg(xr + k) : __ldg(er + (k - 8));
                const uint32_t vv[4] = {v.x, v.y, v.z, v.w};
#pragma unroll
                for (int i = 0; i < 4; i++) {
                    h = fmaf(bf_lo(vv[i]), bf_lo(w[4 * k + i]), h);
                    h = fmaf(bf_hi(vv[i]), bf_hi(w[4 * k + i]), h);
                }
            }
            h *= 0.5f;
            const float f = fmaf(h, tanh_fast(h), h);
            asm volatile("red.shared.add.f32 [%0], %1;" ::"r"(sb + SM_SAGG + (node * 128 + j) * 4), "f"(f) : "memory");
            if (j == 0) atoms_add<1>(sb + SM_DEG + node * 4);
        }
    }
    bar_sync<0, NT>();
    load_w2(sb, tid, NT, a);
    for (int i = tid; i < NPB * 64; i += NT) {
        const int node = i >> 6, pr = i & 63;
        const int hid = (pr >> 3) * 16 + (pr & 7);
        const float u = __uint_as_float(lds32(sb + SM_SAGG + (node * 128 + hid) * 4));
        const float v = __uint_as_float(lds32(sb + SM_SAGG + (node * 128 + hid + 8) * 4));
        const int ch = (pr & 31) >> 2;
        sts32(sb + SM_QA + (pr >> 5) * 24576 + node2row(node) * 128 + ((ch ^ (node & 7)) << 4) + (pr & 3) * 4, pack2(u, v));
    }
    fence_async();
    bar_sync<0, NT>();
    if (wg < 3) tail_gemm<0>(sb, wg, (tid >> 5) & 3, lane, bucket, a.out);
}

template <int MODE>
__device__ __forceinline__ bool producer(uint32_t sb, const Args& a) {
    const int tid = threadIdx.x, lane = tid & 31, warp = tid >> 5, warp4 = warp & 3, u = tid - 512;
    const int cta = blockIdx.x;
    const int nrow = min(NPB, NN - cta * NPB);
    asm volatile("setmaxnreg.dec.sync.aligned.u32 64;");
    const uint32_t ep = MODE == 3 ? ld_g32(a.ctl + 32 + 32 * cta) + 1 : 0;
    auto load_w1 = [&](int j0, int j1) {
        const int r = u >> 4, c = u & 15;
        const uint32_t sw = r * 128 + (((c & 7) ^ r) << 4);
        const __nv_bfloat16* wp = a.w1 + u * 8;
#pragma unroll
        for (int j = j0; j < j1; j++) {
            const uint32_t d = j < 8 ? SM_W1A + j * 1024 : j < 16 ? SM_W1B + (j - 8) * 1024 : SM_W1A + (j - 8) * 1024;
            cp16(sb + d + (c >> 3) * (j < 8 || j >= 16 ? 10240 : 8192) + sw, wp + j * 1024);
        }
    };
    if (MODE & 2) {
        if (u == 32) {
#pragma unroll
            for (int i = 0; i < 4; i++) {
                mbar_init(sb + SM_BAR + i * 8, 128 + 4);
                mbar_init(sb + SM_BAR + 32 + i * 8, 8);
            }
            mbar_init(sb + B_X, 128);
        }
        if (u == 64 && cta == G - 1) { l2_prefetch(a.w2, 16384); l2_prefetch(a.b2, 128); }
        __syncwarp();
    }
    bar_sync<9, 160>();
    {
        const int xrow = u >> 3;
        const uint32_t xa = sb + SM_XO + xrow * 128 + (((u & 7) ^ (xrow & 7)) << 4);
        const __nv_bfloat16* xp = a.x + (size_t)cta * NPB * 64 + (u & 7) * 8;
#pragma unroll
        for (int j = 0; j < 12; j++) cp16z(xa + j * 2048, xp + min(xrow + 16 * j, nrow - 1) * 64, xrow + 16 * j >= nrow);
        cp_commit();
        if (MODE & 2) {
            load_w1(0, 18);
            if (u < 16) cp16(sb + SM_B1 + u * 16, a.b1 + u * 8);
            mbar_cp_arrive(sb + B_X);
        }
        cp_commit();
        cp_wait<1>();
        CSTAMP(20, u == 0);
        if ((MODE & 2) && u == 0) l2_prefetch(a.src + cta * CH, min(CH, NE - cta * CH) * 4);
        __syncwarp();
        if (MODE & 1) {
#pragma unroll
            for (int j0 = 0; j0 < 12; j0 += 6) {
                uint4 v[6];
#pragma unroll
                for (int j = 0; j < 6; j++) v[j] = lds128(xa + (j0 + j) * 2048);
#pragma unroll
                for (int j = 0; j < 6; j++) sts128(sb + SM_XR + u * 16 + (j0 + j) * 2048, bf2h(v[j].x), bf2h(v[j].y), bf2h(v[j].z), bf2h(v[j].w));
            }
            fence_async();
            if (warp4 != 3) bar_arrive<4, MODE == 3 ? 160 : 128>();
        }
        if (MODE & 2) {
            mbar_wait(sb + B_X, 0);
            if (u < 80) {
                uint32_t m = 0;
#pragma unroll
                for (int c = 0; c < 16; c++) {
                    const uint4 v = lds128(sb + SM_W1A + (c >> 3) * 10240 + u * 128 + (((c & 7) ^ (u & 7)) << 4));
                    m = amax2(m, amax2(amax2(v.x, v.y), amax2(v.z, v.w)));
                }
                m = amax_fin(m);
                if (m != 0 && m < 0x3A00u) sts32(sb + F_BAD, 1u);
                asm volatile("red.shared.max.u32 [%0], %1;" ::"r"(sb + F_WMAX), "r"(m) : "memory");
            }
            __syncwarp();
            bar_arrive<3, NT>();
        }
        if ((MODE & 1) && warp4 == 3) {
            bar_sync<4, MODE == 3 ? 160 : 128>();
            if (lane == 0) {
                const int nr = min(NPB, NN + 1 - cta * NPB);
                uint32_t t0 = clock();
#pragma unroll 1
                for (int r = 0; r < nr; r += PROWS) {
                    bulk_store(a.xh + ((size_t)cta * NPB + r) * 8, sb + SM_XR + r * 128, min(PROWS, nr - r) * 128);
                    while (MODE == 3 && (uint32_t)clock() - t0 < PDT) {}
                    t0 += PDT;
                }
                bulk_wait();
                CSTAMP(14, true);
                if (MODE == 3) {
                    asm volatile("red.release.gpu.global.add.u32 [%0], 1;" ::"l"(a.ctl) : "memory");
                    a.ctl[32 + 32 * cta] = ep;
                    CSTAMP(16, true);
                    int it = 0;
                    while ((int)(ld_acq32(a.ctl) - ep * G) < 0)
                        if (++it > (1 << 22)) __trap();
                    CSTAMP(13, true);
                }
            }
            __syncwarp();
        }
    }
    if (!(MODE & 2)) return false;
    const char* xb = reinterpret_cast<const char*>(a.xh) + (lane & 7) * 16;
    const char* eb = reinterpret_cast<const char*>(a.ea) + (lane & 1) * 16;
    const char* sp = reinterpret_cast<const char*>(a.src);
    const int oc = warp4 * 32 + lane;
    const uint32_t posa = sb + SM_POS + col2pos(oc) * 2;
    auto lookup = [&](int t) { return lds32(sb + SM_BIN + lds16(posa + t * 256)); };
    const uint32_t raw = sb + SM_RAW + u * 16, sring = sb + SM_SR + oc * 4;
    auto fetch_s = [&](int slot, uint32_t rec) {
        if (rec & PADW) sts32(sring + slot * 512, NN);
        else cp4(sring + slot * 512, madw(rec & 0xFFFFFu, 4u, sp));
    };
    auto fetch_e = [&](int slot, uint32_t rec) {
        const uint32_t l0 = __shfl_sync(0xFFFFFFFFu, rec, lane >> 1), l1 = __shfl_sync(0xFFFFFFFFu, rec, 16 + (lane >> 1));
        cp16z(raw + slot * 4096, madw(l0 & 0xFFFFFu, 32u, eb), l0 & PADW);
        cp16z(raw + slot * 4096 + 2048, madw(l1 & 0xFFFFFu, 32u, eb), l1 & PADW);
    };
    auto fetch = [&](int slot, uint32_t rec) { fetch_s(slot, rec); fetch_e(slot, rec); };
    const int xc0 = warp4 * 32 + (lane >> 4) * 16 + ((lane >> 3) & 1) * 4;
    const uint32_t slist = sb + SM_SR + xc0 * 4;
    uint32_t xoff[4];
#pragma unroll
    for (int i = 0; i < 4; i++) xoff[i] = sb + SM_XE + (xc0 + i) * 128 + (((lane & 7) ^ ((xc0 + i) & 7)) << 4);
    const int ec = warp4 * 32 + (lane >> 1);
    const uint32_t eoff = sb + SM_XE + 16384 + ec * 32 + (((lane & 1) ^ ((ec >> 2) & 1)) << 4);
    const uint32_t ioff = sb + SM_IND + oc * 32 + (((oc >> 2) & 1) << 4);
    auto put_x = [&](const uint4& la, const uint4& lb, uint32_t so, uint32_t bar) {
        const uint32_t lw[8] = {la.x, la.y, la.z, la.w, lb.x, lb.y, lb.z, lb.w};
#pragma unroll
        for (int i = 0; i < 4; i++) {
            cp16(xoff[i] + so, madw(lw[i], 128u, xb));
            cp16(xoff[i] + so + 1024, madw(lw[4 + i], 128u, xb));
        }
        mbar_cp_arrive(bar);
    };
    auto put_e = [&](const uint32_t* ef, uint32_t cur, uint32_t so, uint32_t ia, uint32_t bar) {
        sts128(eoff + so, ef[0], ef[1], ef[2], ef[3]);
        sts128(eoff + so + 512, ef[4], ef[5], ef[6], ef[7]);
        sts128(ia, 0u, 0u, 0u, 0u);
        sts128(ia ^ 16, 0u, 0u, 0u, 0u);
        if (!(cur & PADW)) sts16(ia ^ ((cur >> 23) & 30u), 0x3C00u);
        __syncwarp();
        if (lane == 0) mbar_arrive(bar);
    };
    asm volatile("" : "+l"(xb), "+l"(eb), "+l"(sp));
    __syncwarp();
    bar_sync<5, NT>();
    const uint4 fl = lds128(sb + F_TOT);
    const uint32_t p0 = lds16(posa), p1 = lds16(posa + 256);
    const int T = fl.z ? 0 : ((int)fl.x + 63) >> 6;
    CSTAMP(17, u == 0 && T >= 0);
    const int T0 = (T + 1) >> 1, T1 = T >> 1;
    uint32_t own[4] = {PADW, PADW, PADW, PADW};
    if (T > 0) own[0] = lds32(sb + SM_BIN + p0);
    if (T > 1) own[1] = lookup(T - 1);
    if (T > 2) own[2] = lds32(sb + SM_BIN + p1);
    if (T > 3) own[3] = lookup(T - 2);
    fetch_e(0, own[0]);
    fetch_e(1, own[1]);
    cp_commit();
    CSTAMP(18, u == 0);
    uint32_t nx[2] = {PADW, PADW};
    if (T > 4) nx[0] = lookup(2);
    if (T > 5) nx[1] = lookup(T - 3);
    bar_sync<6, NT>();
    if (lds32(sb + F_BAD)) {
        cp_wait_all();
        asm volatile("setmaxnreg.inc.sync.aligned.u32 96;");
        return true;
    }
    if (T > 0) {
        fetch(2, own[2]);
        cp_commit();
        fetch(3, own[3]);
        cp_commit();
        cp_commit();
        cp_commit();
        cp_wait<4>();
        CSTAMP(21, u == 0);
        uint32_t ef[2][8];
#pragma unroll
        for (int s = 0; s < 2; s++) {
            const uint4 e0 = lds128(raw + s * 4096), e1 = lds128(raw + s * 4096 + 2048);
            const uint32_t w[8] = {e0.x, e0.y, e0.z, e0.w, e1.x, e1.y, e1.z, e1.w};
#pragma unroll
            for (int i = 0; i < 8; i++) ef[s][i] = w[i];
        }
#pragma unroll
        for (int s = 0; s < 2; s++) {
#pragma unroll
            for (int i = 0; i < 8; i++) ef[s][i] = bf2h(ef[s][i]);
            if (s < T) put_e(ef[s], own[s], s * XE_S, ioff + s * 4096, sb + SM_BAR + s * 16);
        }
#pragma unroll
        for (int s = 0; s < 2; s++) {
            own[s] = own[2 + s];
            own[2 + s] = nx[s];
        }
    }
    CSTAMP(26, u == 0);
    int i3 = 8192;
    for (int k = 1; k < T0; k++) {
#pragma unroll
        for (int s = 0; s < 2; s++) {
            if (s == 1 && k >= T1) break;
            const int tn = s ? T - 3 - k : k + 2, st = 2 * s + (k & 1), slot = 2 * (k & 1) + s;
            const bool more = k + 2 < (s ? T1 : T0);
            const uint32_t cur = own[s];
            own[s] = own[2 + s];
            if (more) own[2 + s] = lookup(tn);
            cp_wait<3>();
            __syncwarp();
            const uint4 la = lds128(slist + slot * 512), lb = lds128(slist + slot * 512 + 32);
            const uint4 e0 = lds128(raw + slot * 4096), e1 = lds128(raw + slot * 4096 + 2048);
            const uint32_t ef[8] = {bf2h(e0.x), bf2h(e0.y), bf2h(e0.z), bf2h(e0.w), bf2h(e1.x), bf2h(e1.y), bf2h(e1.z), bf2h(e1.w)};
            const uint32_t ia = ioff + i3 + s * 4096;
            const uint32_t so = s * XE_S + (k & 1) * XE_P;
            mbar_wait(sb + SM_BAR + 32 + st * 8, ((k >> 1) & 1) ^ 1);
            put_x(la, lb, so, sb + SM_BAR + st * 8);
            put_e(ef, cur, so, ia, sb + SM_BAR + st * 8);
            if (more || k == 1) fetch(k == 1 ? s : slot, k == 1 ? own[s] : own[2 + s]);
            cp_commit();
        }
        if (k == 1) {
            if (3 < T0) fetch(2, own[2]);
            cp_commit();
            if (3 < T1) fetch(3, own[3]);
            cp_commit();
        }
        i3 = (i3 == 16384) ? 0 : i3 + 8192;
    }
    cp_wait_all();
    bar_sync<10, 128>();
    load_w2(sb, u, 128, a);
    fence_async();
    bar_sync<1, NT>();
    tail_scan(sb, u + 128);
    if (!tail_failed(sb) || T == 0) return false;
    asm volatile("setmaxnreg.inc.sync.aligned.u32 96;");
    return true;
}

template <int MODE>
__device__ __forceinline__ bool consumer(uint32_t sb, const Args& a) {
    const int tid = threadIdx.x, lane = tid & 31, warp = tid >> 5, wg = tid >> 7, warp4 = warp & 3;
    const int cta = blockIdx.x;
    uint32_t ep = 1;
    {
        const int nv = min(CH, NE - cta * CH) >> 2;
        uint4 dv[3];
        if (MODE == 3) ep = ld_g32(a.ctl + 32 + 32 * cta);
        if (MODE & 1) {
            const int* dp = a.dst + cta * CH + tid * 4;
            dv[0] = ld_stream(dp);
            dv[1] = ld_stream(dp + 2048);
            dv[2] = ld_stream(tid + 1024 < nv ? dp + 4096 : dp);
        }
        if (tid >= 8 && tid < 16) sts32(sb + SM_FLAG + (tid - 8) * 4, 0u);
        if (tid == 16) sts32(sb + SM_BIN + PADO, PADW);
        __syncwarp();
        if ((XAT < 0 || !(MODE & 1)) && warp == 0) bar_sync<9, 160>();
        if (tid >= 64 && tid < 288)
            sts32(sb + SM_DEG + (tid - 64) * 4, tid >= 256 ? 0xC0000000u : (1u << 18) + sb + SM_BIN + (tid - 64 < NPB ? (tid - 64) * BINP : PADO));
        else if (tid >= 288 && tid < 288 + G) sts32(sb + SM_CNT + (tid - 288) * 4, sb + SM_STA + (tid - 288 + (tid - 288 < cta ? G : 0) - cta) * RP);
        if (MODE == 3) ep++;
        const uint32_t tg = ((ep & 255u) + 256u) << 13;
        if (MODE & 1) {
            const uint32_t pw = tg + 0xC0000000u + (lane << 24);
#pragma unroll
            for (int j = 0; j < 5; j++)
                if (tid + 512 * j < G * RU) sts128(sb + SM_STA + tid * 16 + j * 8192, pw, pw, pw, pw);
        }
        CSTAMP(22, tid == 0);
        bar_sync<2, 512>();
        if (MODE & 1) {
            uint32_t mask = 0, inc = CINC;
            asm volatile("" : "+r"(inc));
#pragma unroll
            for (int j = 0; j < 3; j++)
                if (j < 2 || tid + 1024 < nv) {
                    const uint32_t dd[4] = {dv[j].x, dv[j].y, dv[j].z, dv[j].w};
                    uint32_t w[4], pa[4];
#pragma unroll
                    for (int k = 0; k < 4; k++) {
                        const uint32_t b = __umulhi(dd[k], 22605092u);
                        pa[k] = atoms_addr(sb + SM_CNT + b * 4, inc);
                        w[k] = (dd[k] << 24) + (tg + tid * 4 + j * 2048 + k) - b * ((uint32_t)NPB << 24);
                    }
                    if (j == XAT && warp == 0) bar_sync<9, 160>();
                    if (j == 0) CSTAMP(2, tid == 0);
                    put<RUNL, 1u>(pa[0], w[0], mask);
                    put<RUNL, 2u>(pa[1], w[1], mask);
                    put<RUNL, 4u>(pa[2], w[2], mask);
                    put<RUNL, 8u>(pa[3], w[3], mask);
                    mask <<= 4;
                }
            if (__builtin_expect(mask != 0, 0)) send_extra(sb, tid + 1024 < nv ? mask : mask << 4, ep, a);
            CSTAMP(3, tid == 0);
            fence_async();
            __syncwarp();
            bar_sync<2, 512>();
            if (tid == 0) {
                bulk_store(a.ra + (size_t)cta * (G * RU), sb + SM_STA, G * RP);
                if (MODE == 1) bulk_wait();
            }
            __syncwarp();
        }
    }
    if (!(MODE & 2)) return false;
    asm volatile("setmaxnreg.inc.sync.aligned.u32 104;");
    CSTAMP(4, tid == 0);
    const int s = wg >> 1, h = wg & 1;
    uint32_t w1f[5][4];
    mbar_wait(sb + B_X, 0);
    fence_async();
    {
        float d[48];
        const float ba = 0.5f * bf_lo(lds16(sb + SM_B1 + (h * 64 + warp4 * 16 + (lane >> 2)) * 2));
        const float bb = 0.5f * bf_lo(lds16(sb + SM_B1 + (h * 64 + warp4 * 16 + (lane >> 2)) * 2 + 16));
        q_gemm(d, mkdesc(sb + SM_W1B + h * 8192, 16, 1024, 1), mkdesc(sb + SM_XO + s * 12288, 16, 1024, 1));
        const uint32_t qa = sb + SM_QA + h * 24576 + (lane >> 4) * 12288 + s * 6144 + (lane & 7) * 128 +
                            (((2 * warp4 + ((lane >> 3) & 1)) ^ (lane & 7)) << 4);
#pragma unroll
        for (int j = 0; j < 6; j++) {
            const float* e = d + 8 * j;
            stsm4t(qa + j * 1024, pack2h(fmaf(e[0], 0.5f, ba), fmaf(e[1], 0.5f, ba)), pack2h(fmaf(e[2], 0.5f, bb), fmaf(e[3], 0.5f, bb)),
                   pack2h(fmaf(e[4], 0.5f, ba), fmaf(e[5], 0.5f, ba)), pack2h(fmaf(e[6], 0.5f, bb), fmaf(e[7], 0.5f, bb)));
        }
    }
    fence_async();
    CSTAMP(19, tid == 0);
    {
        const int kr = (lane & 7) + 8 * (lane >> 4), ch = 2 * warp4 + ((lane >> 3) & 1);
#pragma unroll
        for (int ks = 0; ks < 5; ks++) {
            ldsm4t(w1f[ks], sb + SM_W1A + h * 10240 + (16 * ks + kr) * 128 + ((ch ^ (kr & 7)) << 4));
#pragma unroll
            for (int i = 0; i < 4; i++) w1f[ks][i] = pack2h(0.5f * bf_lo(w1f[ks][i]), 0.5f * bf_hi(w1f[ks][i]));
        }
    }
    {
        const uint32_t tg = ((ep & 255u) + 256u) << 13, pw = tg + 0xC0000000u + (lane << 24);
        uint32_t inc = CINC, i = tid, run;
        asm volatile("" : "+r"(inc));
        auto unit = [&](uint32_t i) {
            const uint32_t r = __umulhi(i, 226050911u);
            run = cta - r + (r > cta ? G : 0);
            return a.ra + (run * (G * RU) + i);
        };
        const uint4* gn = unit(i);
        if (MODE == 3) {
            if (tid == 0) bulk_wait_read();
            __syncwarp();
            bar_sync<2, 512>();
        }
        if (MODE == 3 && PUBR < 0 && warp == 3) bar_arrive<4, 160>();
        CSTAMP(24, tid == 0);
        uint4 nx = ld_rec(gn);
#pragma unroll 1
        do {
            uint4 rv = nx, v;
            const uint4* ga = gn;
            const uint32_t from = run, c0 = run * CH - tg;
            gn = unit(min(i + 512, G * RU - 1));
            if (MODE == 3) {
                int it = 0;
                while (__builtin_expect(__any_sync(0xFFFFFFFFu, ((rv.x ^ tg) | (rv.y ^ tg) | (rv.z ^ tg) | (rv.w ^ tg)) & TAGM), 0)) {
                    if (++it > (1 << 22)) __trap();
                    rv = ld_rec(ga);
                }
            }
            if (i < 2048) nx = ld_rec(gn);
            CSTAMP(23, tid == 0 && i == 0);
            CSTAMP(25, tid == 0 && i == 2048);
            if (i >= G * RU) rv.x = rv.y = rv.z = rv.w = pw;
            v.x = atoms_addr(sb + SM_DEG + (rv.x >> 22), inc);
            v.y = atoms_addr(sb + SM_DEG + (rv.y >> 22), inc);
            v.z = atoms_addr(sb + SM_DEG + (rv.z >> 22), inc);
            v.w = atoms_addr(sb + SM_DEG + (rv.w >> 22), inc);
            const bool ext = (rv.w ^ pw) - 1u < 0x1FFFu;
            put<BINL>(v.x, rv.x + c0);
            put<BINL>(v.y, rv.y + c0);
            put<BINL>(v.z, rv.z + c0);
            put<BINL>(v.w, rv.w + c0);
            if (__builtin_expect(max(max((int)v.x, (int)v.y), max((int)v.z, (int)v.w)) >= (int)BINL || ext, 0)) {
                if ((int)v.x >= (int)BINL) bin_overflow(sb, rv.x + c0, v.x);
                if ((int)v.y >= (int)BINL) bin_overflow(sb, rv.y + c0, v.y);
                if ((int)v.z >= (int)BINL) bin_overflow(sb, rv.z + c0, v.z);
                if ((int)v.w >= (int)BINL) bin_overflow(sb, rv.w + c0, v.w);
                if (ext) recv_extra<MODE>(sb, rv.w & 0x1FFFu, from, ep, a);
            }
            __syncwarp();
            if (MODE == 3 && (i >> 5) == PUBR * 16 + 3) bar_arrive<4, 160>();
            i += 512;
        } while (i < 2560);
    }
    CSTAMP(7, tid == 0);
    bar_sync<3, NT>();
    int T;
    uint4 xv[4];
    {
        uint32_t c[6], tot = 0, bef = 0;
#pragma unroll
        for (int j = 0; j < 6; j++) c[j] = lds32(sb + SM_DEG + lane * 4 + j * 128) >> 19;
        const uint32_t own = lds32(sb + SM_DEG + min(warp * 12 + lane, 191) * 4);
        const uint32_t bad = lds32(sb + F_BAD), no = lds32(sb + F_XC);
        CSTAMP(6, tid == 0 && own != 1);
#pragma unroll
        for (int j = 0; j < 6; j++) {
            tot += c[j];
            if (lane + 32 * j < warp * 12) bef += c[j];
        }
        uint32_t inc = own >> 19;
#pragma unroll
        for (int o = 1; o < 16; o <<= 1) {
            const uint32_t w = __shfl_up_sync(0xFFFFFFFFu, inc, o);
            if (lane >= o) inc += w;
        }
        tot = __reduce_add_sync(0xFFFFFFFFu, tot);
        bef = __reduce_add_sync(0xFFFFFFFFu, bef);
        const uint32_t pk = ((bef + inc - (own >> 19)) << 16) + (own >> 18);
        T = (tot + 63) >> 6;
        if (bad == 0 && tot <= CAP / 2) {
            if (lane < 12 && own < BINL + (1u << 18)) sts32(own & 0x3FFFFu, PADW);
            const int l8 = lane & 7;
            const uint32_t val = ((warp * 12 + (lane >> 3)) * BINP + l8 * 8) * 0x10001u + 0x40000u;
#pragma unroll
            for (int r = 0; r < 3; r++) {
                const uint32_t e = __shfl_sync(0xFFFFFFFFu, pk, 4 * r + (lane >> 3));
                const uint32_t ad = sb + SM_POS + (e >> 16) * 4 + l8 * 4, lim = (e & 0xFFFFu) - 2 * l8;
#pragma unroll
                for (int i = 0; i < 3; i++)
                    if ((int)lim > 16 * i + 1) sts32(ad + 32 * i, val + (uint32_t)(r * 4 * BINP + 64 * i) * 0x10001u);
            }
            if (tid < 64 && tot + tid < T * 64) sts32(sb + SM_POS + (tot + tid) * 4, PADO * 0x10001u);
            if (no) {
                if (lane < 12 && own >= BINL && !(own & (1u << 18))) sts16(sb + SM_POS + (pk >> 16) * 4 + (pk & 0xFFFFu) * 2 - 2, PADO);
#pragma unroll 1
                for (uint32_t i = 0; i < no; i += 32) {
                    const uint2 o = lds64(sb + SM_OVL + min(i + lane, OVC - 1u) * 8);
                    const uint32_t n = (o.x >> 24) - warp * 12, e = __shfl_sync(0xFFFFFFFFu, pk, n);
                    if (i + lane < no && n < 12) sts16(sb + SM_POS + (e >> 16) * 4 + (o.y >> 18) * 2 - 2, OVLO + (i + lane) * 8);
                }
            }
        } else if (tid == 0) sts32(sb + F_BAD, 1u);
        if (tid == 0) sts32(sb + F_TOT, tot);
        __syncwarp();
        CSTAMP(8, tid == 0);
        bar_sync<5, NT>();
        {
            uint32_t sv[4] = {NN, NN, NN, NN};
            if (bad == 0 && tot <= CAP / 2 && s < T) {
                const uint2 po = lds64(sb + SM_POS + (s ? T - 1 : 0) * 256 + (warp & 7) * 32 + (lane >> 3) * 8);
                const uint32_t rec[4] = {lds32(sb + SM_BIN + (po.x & 0xFFFFu)), lds32(sb + SM_BIN + (po.x >> 16)),
                                         lds32(sb + SM_BIN + (po.y & 0xFFFFu)), lds32(sb + SM_BIN + (po.y >> 16))};
#pragma unroll
                for (int j = 0; j < 4; j++) sv[j] = ld_src(a.src, rec[j]);
            }
#pragma unroll
            for (int j = 0; j < 4; j++) xv[j] = ld_row(a.x + (lane & 7) * 8, sv[j]);
        }
        CSTAMP(5, tid == 64);
        if (tid < T && lds32(sb + F_BAD) == 0) {
            const int T0 = (T + 1) >> 1;
            const uint32_t first = lds32(sb + SM_BIN + lds16(sb + SM_POS + tid * 256)) >> 24;
            const uint32_t last = lds32(sb + SM_BIN + lds16(sb + SM_POS + min(tid * 64u + 63u, tot - 1) * 4)) >> 24;
            const uint32_t w = min(first >> 3, 22u), ta = sb + SM_TT + (tid < T0 ? tid : 32 + T - 1 - tid) * 16;
            sts32(ta + 4, dlo(sb + SM_QA + ((w + 1) >> 1) * 1024));
            sts32(ta + 8, ((12288 - (w & 1) * 1024) >> 4) | (1u << 30));
            sts32(ta, (tid < T0 ? first : last) * 64);
            if (tid == T0) {
                sts32(sb + SM_TT + T0 * 16, first * 64);
                sts32(sb + SM_TT + (32 + T - T0) * 16, first * 64);
            }
            if (T == 1) sts32(sb + SM_TT + 16, NPB * 64);
            if ((last >> 3) > w + 1) sts32(sb + F_BAD, 1u);
        }
        if (warp == 2) {
            const uint32_t m = __reduce_max_sync(0xFFFFFFFFu, max(max(max(c[0], c[1]), max(c[2], c[3])), max(c[4], c[5])));
            if (lane == 0) sts32(sb + F_DMAX, 2 * m);
        }
        __syncwarp();
    }
    bar_arrive<6, NT>();
    bar_sync<2, 512>();
    if (lds32(sb + F_BAD)) {
        asm volatile("setmaxnreg.dec.sync.aligned.u32 96;");
        return true;
    }

    {
        const int wgu = __shfl_sync(0xFFFFFFFFu, wg, 0), Tu = __shfl_sync(0xFFFFFFFFu, T, 0);
        const int su = wgu >> 1, hu = wgu & 1;
        const int Ts = su ? Tu >> 1 : (Tu + 1) >> 1;
        if (Ts > 0) {
            const int q = lane & 3;
            const uint32_t a0 = q * 256 + (((2 * warp4 + (lane >> 4)) ^ (2 * q)) << 4) + ((lane >> 2) & 3) * 4, a1 = (a0 + 128) ^ 16;
            const uint32_t c0 = sb + SM_QA + hu * 24576 + (su ? 0 : 960) - 128 * q;
            uint32_t acc[32], pk[16], fa[4];
            float agg[8];
#pragma unroll
            for (int i = 0; i < 8; i++) agg[i] = 0.f;
#pragma unroll
            for (int i = 0; i < 16; i++) pk[i] = 0u;
            auto flush = [&](uint32_t F, bool on) {
                const uint32_t v = F + c0;
#pragma unroll
                for (int j = 0; j < 4; j++) {
                    const int i0 = (j >> 1) * 4 + (j & 1);
                    const uint32_t t = v - 64 * (j & 1) - 512 * (j >> 1);
                    if (on && ((t ^ fa[j]) & ~1023u)) {
                        sts32(fa[j] + (j >> 1) * 12288, pack2(agg[i0], agg[i0 + 2]));
                        agg[i0] = 0.f;
                        agg[i0 + 2] = 0.f;
                    }
                    asm("lop3.b32 %0, %1, %0, 1023, 0xD8;" : "+r"(fa[j]) : "r"(t));
                }
            };
            fa[0] = fa[2] = a0;
            fa[1] = fa[3] = a1;
            const uint32_t tta = sb + SM_TT + su * 512;
            uint4 tt = lds128(tta);
            flush(tt.x, false);
            const uint32_t ifirst = dlo(sb + SM_IND + su * 4096), ilast = ifirst + 1024;
            uint32_t iprev = ifirst, icur = ifirst;
            const uint32_t x0 = dlo(sb + SM_XE + su * XE_S), bar0 = sb + SM_BAR + 2 * su * 8;
            {
                const uint32_t xa = sb + SM_XE + su * XE_S + ((warp & 7) * 16 + (lane >> 3) * 2) * 128 + (((lane & 7) ^ ((lane >> 3) * 2)) << 4);
#pragma unroll
                for (int j = 0; j < 4; j++)
                    sts128((xa + (j & 1) * 1024 + (j >> 1) * 128) ^ ((j >> 1) << 4), bf2h(xv[j].x), bf2h(xv[j].y), bf2h(xv[j].z), bf2h(xv[j].w));
                __syncwarp();
                if (elect()) asm volatile("mbarrier.arrive.shared::cta.b64 _, [%0], 16;" ::"r"(bar0) : "memory");
                CSTAMP(27, tid == 64);
            }
            for (int k = 0; k < Ts; k++) {
                const uint32_t dx = x0 + (k & 1) * (XE_P >> 4), bar = bar0 + (k & 1) * 8;
                mbar_wait(bar, (k >> 1) & 1);
                fence_async();
                wg_fence();
#pragma unroll
                for (int kk = 0; kk < 4; kk++) r16t(agg, pk + 4 * kk, dsc(iprev + kk * 64, DH32A));
                wg_commit();
                h128z(acc, w1f[0], dsc(dx, DH128));
                h128(acc, w1f[1], dsc(dx + 2, DH128));
                h128(acc, w1f[2], dsc(dx + 4, DH128));
                h128(acc, w1f[3], dsc(dx + 6, DH128));
                h128(acc, w1f[4], dsc(dx + 1024, DH32B));
                h128s(acc, dsc(tt.y + hu * 1536, tt.z), dsc(icur, DH32B));
                wg_commit();
                wg_wait<1>();
                fence_regs<8>(agg);
                fence_regs<16>(pk);
                flush(tt.x, true);
                tt = lds128(tta + (k + 1) * 16);
                wg_wait<0>();
                fence_regs<32>(acc);
                if (elect()) mbar_arrive(bar + 32);
#pragma unroll
                for (int i = 0; i < 16; i++) {
                    const int i0 = (i >> 1) * 4 + (i & 1);
                    pk[i] = hadd2(silu_h2(acc[i0]), silu_h2(acc[i0 + 2]));
                }
                fence_regs<16>(pk);
                iprev = icur;
                icur = icur == ilast ? ifirst : icur + 512;
            }
            wg_fence();
#pragma unroll
            for (int kk = 0; kk < 4; kk++) r16t(agg, pk + 4 * kk, dsc(iprev + kk * 64, DH32A));
            wg_commit();
            wg_wait<0>();
            fence_regs<8>(agg);
            flush(tt.x, true);
            if (Tu > 1) {
                const int sl = (tt.x >> 6) & 15;
                const bool mine = q == ((sl & 7) >> 1);
                const uint32_t xa = sb + SM_XB + hu * 256 + (warp4 * 8 + (lane >> 2)) * 8;
                const float v0 = (sl & 8) ? ((sl & 1) ? agg[5] : agg[4]) : ((sl & 1) ? agg[1] : agg[0]);
                const float v1 = (sl & 8) ? ((sl & 1) ? agg[7] : agg[6]) : ((sl & 1) ? agg[3] : agg[2]);
                if (su) {
                    if (mine) sts64(xa, __float_as_uint(v0), __float_as_uint(v1));
                    if (hu) bar_arrive<8, 256>(); else bar_arrive<7, 256>();
                } else {
                    if (hu) bar_sync<8, 256>(); else bar_sync<7, 256>();
                    const uint32_t ra = (sl & 8) ? ((sl & 1) ? fa[3] : fa[2]) + 12288 : ((sl & 1) ? fa[1] : fa[0]);
                    if (mine) sts32(ra, pack2(v0 + __uint_as_float(lds32(xa)), v1 + __uint_as_float(lds32(xa + 4))));
                }
            }
        }
    }
    CSTAMP(10, tid == 0);
    fence_async();
    bar_sync<1, NT>();
    if (wg < 3) tail_gemm<1>(sb, wg, warp4, lane, cta, a.out);
    else tail_scan(sb, tid - 384);
    CSTAMP(15, tid == 0);
    if (!tail_failed(sb) || T == 0) return false;
    asm volatile("setmaxnreg.dec.sync.aligned.u32 96;");
    return true;
}

template <int MODE>
__global__ void __launch_bounds__(NT, 1) mpnn_kernel(const __grid_constant__ Args a) {
    extern __shared__ __align__(1024) uint8_t smem[];
    const uint32_t sb = (uint32_t)__cvta_generic_to_shared(smem);
    TSTAMP(0, threadIdx.x == 0);
    CSTAMP(1, threadIdx.x == 0);
    const bool slow = threadIdx.x >= 512 ? producer<MODE>(sb, a) : consumer<MODE>(sb, a);
    if ((MODE & 2) && slow) slow_path(sb, blockIdx.x, a);
    CSTAMP(11, threadIdx.x == 0);
    TSTAMP(12, threadIdx.x == 0);
}

}

extern "C" void kernel_launch(void* const* d_in, const int* in_sizes, int n_in, void* d_out, int out_size) {
    (void)in_sizes; (void)n_in; (void)out_size;
    static int fused = -1;
    static void *p_ra, *p_rx, *p_xh, *p_ctl;
    if (fused < 0) {
        cudaGetSymbolAddress(&p_ra, g_ra);
        cudaGetSymbolAddress(&p_rx, g_rx);
        cudaGetSymbolAddress(&p_xh, g_xh);
        cudaGetSymbolAddress(&p_ctl, g_ctl);
        int dev = 0, sms = 0, nb = 0;
        cudaGetDevice(&dev);
        cudaDeviceGetAttribute(&sms, cudaDevAttrMultiProcessorCount, dev);
        cudaFuncSetAttribute(mpnn_kernel<1>, cudaFuncAttributeMaxDynamicSharedMemorySize, SM_TOTAL);
        cudaFuncSetAttribute(mpnn_kernel<2>, cudaFuncAttributeMaxDynamicSharedMemorySize, SM_TOTAL);
        cudaFuncSetAttribute(mpnn_kernel<3>, cudaFuncAttributeMaxDynamicSharedMemorySize, SM_TOTAL);
        cudaOccupancyMaxActiveBlocksPerMultiprocessor(&nb, mpnn_kernel<3>, NT, SM_TOTAL);
        fused = (sms * nb >= G) ? 1 : 0;
    }
    Args a;
    a.x   = (const __nv_bfloat16*)d_in[0];
    a.ea  = (const __nv_bfloat16*)d_in[1];
    a.src = (const int*)d_in[2];
    a.dst = (const int*)d_in[3];
    a.w1  = (const __nv_bfloat16*)d_in[4];
    a.b1  = (const __nv_bfloat16*)d_in[5];
    a.w2  = (const __nv_bfloat16*)d_in[6];
    a.b2  = (const __nv_bfloat16*)d_in[7];
    a.out = (__nv_bfloat16*)d_out;
    a.ra  = (uint4*)p_ra;
    a.rx  = (uint2*)p_rx;
    a.xh  = (uint4*)p_xh;
    a.ctl = (uint32_t*)p_ctl;
    cudaStream_t s = cudaStreamPerThread;
    if (fused) {
        mpnn_kernel<3><<<G, NT, SM_TOTAL, s>>>(a);
    } else {
        mpnn_kernel<1><<<G, NT, SM_TOTAL, s>>>(a);
        mpnn_kernel<2><<<G, NT, SM_TOTAL, s>>>(a);
    }
}
```

```cpp
#include <cuda_runtime.h>
#include <cuda_bf16.h>
#include <stdint.h>

#define RELX 0
#define PUBR -1
#define PDT 220
#define PROWS 16
#define KF 2
#define FP 2
#define XAT 0
namespace {

constexpr int NN   = 25000;
constexpr int NE   = 800000;
constexpr int G    = 132;
constexpr int NPB  = 190;
constexpr int CH   = 6064;
constexpr int CAPT = 52;
constexpr int CAP  = CAPT * 128;
constexpr int NT   = 640;
constexpr int CAPB = 48;
constexpr int OVC  = 64;
constexpr int BINP = CAPB * 4 + 4;
constexpr int RP   = 304;
constexpr int RS   = RP / 4 - 1, RU = RP / 16, RX = 32;
constexpr uint32_t CINC = (1u << 18) + 4u;
constexpr uint32_t RUNL = (uint32_t)RS << 18, BINL = (uint32_t)(CAPB + 1) << 18;
constexpr uint32_t TAGM = 511u << 13, PADW = 0x800000u;

constexpr int SM_CNT  = 0;
constexpr int SM_DEG  = 576;
constexpr int SM_FLAG = SM_DEG + 896;
constexpr int SM_TT   = SM_FLAG + 32;
constexpr int SM_XB   = SM_TT + 1024;
constexpr int SM_B1   = SM_XB + 512;
constexpr int SM_B2   = SM_B1 + 256;
constexpr int SM_BAR  = SM_B2 + 128;
constexpr int SM_XE   = 5120;
constexpr int XE_S    = 20480, XE_P = 65536;
constexpr int SM_IND  = SM_XE + 2 * XE_S;
constexpr int SM_POS  = SM_XE + XE_P + 2 * XE_S;
constexpr int SM_RAW  = 126976;
constexpr int SM_QA   = SM_RAW + 16384;
constexpr int SM_BIN  = SM_QA + 49152;
constexpr int SM_OVL  = SM_BIN + NPB * BINP;
constexpr int SM_SR   = SM_OVL + OVC * 8 + 8;
constexpr int SM_TOTAL = SM_SR + 2048;
constexpr uint32_t OVLO = SM_OVL - SM_BIN, PADO = OVLO + OVC * 8;
constexpr int F_TOT = SM_FLAG, F_DMAX = SM_FLAG + 4, F_BAD = SM_FLAG + 8, F_WMAX = SM_FLAG + 12, F_NF = SM_FLAG + 16,
              F_BIG = SM_FLAG + 20, F_XC = SM_FLAG + 28;
constexpr int SM_STA  = SM_XE;
constexpr int SM_XO   = SM_IND;
constexpr int SM_XR   = SM_XE + XE_P;
constexpr int SM_W1B  = SM_XR + 24576;
constexpr int SM_W1A  = SM_POS;
constexpr int B_X = SM_BAR + 64;
constexpr int SM_W2   = SM_BIN;
constexpr int SM_SAGG = SM_XE;
constexpr int SM_SQ   = SM_SAGG + NPB * 512;
static_assert(B_X + 8 <= SM_XE && SM_IND + 24576 == SM_XE + XE_P && SM_POS + CAP * 2 <= SM_RAW && SM_STA + G * RP <= SM_IND, "map");
static_assert(SM_W1B + 16384 <= SM_POS && SM_W1A + 20480 <= SM_QA, "map");
static_assert(SM_SQ <= SM_QA && SM_SQ + NPB * 512 <= SM_TOTAL && SM_TOTAL <= 232448 && PADO < 65536, "map");
static_assert(G * (RS + RX) + 2 < 16384 && G * RU <= 5 * 512 && G * CH >= NE && NE - (G - 1) * CH > 4096 && CH <= 6144 && CH % 4 == 0, "fields");
static_assert(SM_W2 % 1024 == 0 && SM_QA % 1024 == 0 && SM_XO % 1024 == 0 && SM_W1A % 1024 == 0 && SM_W1B % 1024 == 0 &&
              SM_B1 % 16 == 0 && SM_TT % 16 == 0 && SM_BAR % 8 == 0 && SM_STA % 16 == 0 && SM_OVL % 8 == 0 && SM_XR % 16 == 0 && SM_SR % 16 == 0 && SM_DEG % 16 == 0, "align");

__device__ uint4 g_ra[G * G * RU];
__device__ uint2 g_rx[G * G * RX];
__device__ uint4 g_xh[(NN + 1) * 8];
__device__ uint32_t g_ctl[(G + 1) * 32];
#define CSTAMPV(i, cond)
#define TSTAMP(i, cond)
#define CSTAMP(i, cond)

__device__ __forceinline__ uint64_t mkdesc(uint32_t addr, uint32_t lbo, uint32_t sbo, uint32_t swz) {
    return (uint64_t)((addr & 0x3FFFF) >> 4) | ((uint64_t)(lbo >> 4) << 16) | ((uint64_t)(sbo >> 4) << 32) |
           ((uint64_t)swz << 62);
}
__device__ __forceinline__ void wg_fence()  { asm volatile("wgmma.fence.sync.aligned;" ::: "memory"); }
__device__ __forceinline__ void wg_commit() { asm volatile("wgmma.commit_group.sync.aligned;" ::: "memory"); }
template <int N> __device__ __forceinline__ void wg_wait() { asm volatile("wgmma.wait_group.sync.aligned %0;" ::"n"(N) : "memory"); }
__device__ __forceinline__ void fence_async() { asm volatile("fence.proxy.async.shared::cta;" ::: "memory"); }

#define R8(d, o) "+f"(d[o + 0]), "+f"(d[o + 1]), "+f"(d[o + 2]), "+f"(d[o + 3]), "+f"(d[o + 4]), "+f"(d[o + 5]), "+f"(d[o + 6]), "+f"(d[o + 7])
#define W8(d, o) "=f"(d[o + 0]), "=f"(d[o + 1]), "=f"(d[o + 2]), "=f"(d[o + 3]), "=f"(d[o + 4]), "=f"(d[o + 5]), "=f"(d[o + 6]), "=f"(d[o + 7])
#define U8(d, o) "+r"(d[o + 0]), "+r"(d[o + 1]), "+r"(d[o + 2]), "+r"(d[o + 3]), "+r"(d[o + 4]), "+r"(d[o + 5]), "+r"(d[o + 6]), "+r"(d[o + 7])
#define V8(d, o) "=r"(d[o + 0]), "=r"(d[o + 1]), "=r"(d[o + 2]), "=r"(d[o + 3]), "=r"(d[o + 4]), "=r"(d[o + 5]), "=r"(d[o + 6]), "=r"(d[o + 7])
#define L32 "{%0,%1,%2,%3,%4,%5,%6,%7,%8,%9,%10,%11,%12,%13,%14,%15,%16,%17,%18,%19,%20,%21,%22,%23,%24,%25,%26,%27,%28,%29,%30,%31}"
#define L48 "{%0,%1,%2,%3,%4,%5,%6,%7,%8,%9,%10,%11,%12,%13,%14,%15,%16,%17,%18,%19,%20,%21,%22,%23,%24,%25,%26,%27,%28,%29,%30,%31,%32,%33,%34,%35,%36,%37,%38,%39,%40,%41,%42,%43,%44,%45,%46,%47}"

__device__ __forceinline__ void h128z(uint32_t* d, const uint32_t* a, uint64_t db) {
    asm volatile("{.reg .pred p; setp.ne.b32 p, 0, 0;\n"
                 "wgmma.mma_async.sync.aligned.m64n128k16.f16.f16.f16 " L32 ", {%32,%33,%34,%35}, %36, p, 1, 1, 0;}"
                 : V8(d, 0), V8(d, 8), V8(d, 16), V8(d, 24) : "r"(a[0]), "r"(a[1]), "r"(a[2]), "r"(a[3]), "l"(db));
}
__device__ __forceinline__ void h128(uint32_t* d, const uint32_t* a, uint64_t db) {
    asm volatile("{.reg .pred p; setp.eq.b32 p, 0, 0;\n"
                 "wgmma.mma_async.sync.aligned.m64n128k16.f16.f16.f16 " L32 ", {%32,%33,%34,%35}, %36, p, 1, 1, 0;}"
                 : U8(d, 0), U8(d, 8), U8(d, 16), U8(d, 24) : "r"(a[0]), "r"(a[1]), "r"(a[2]), "r"(a[3]), "l"(db));
}
__device__ __forceinline__ void h128s(uint32_t* d, uint64_t da, uint64_t db) {
    asm volatile("{.reg .pred p; setp.eq.b32 p, 0, 0;\n"
                 "wgmma.mma_async.sync.aligned.m64n128k16.f16.f16.f16 " L32 ", %32, %33, p, 1, 1, 1, 0;}"
                 : U8(d, 0), U8(d, 8), U8(d, 16), U8(d, 24) : "l"(da), "l"(db));
}
__device__ __forceinline__ void r16t(float* d, const uint32_t* a, uint64_t db) {
    asm volatile("{.reg .pred p; setp.eq.b32 p, 0, 0;\n"
                 "wgmma.mma_async.sync.aligned.m64n16k16.f32.f16.f16 {%0,%1,%2,%3,%4,%5,%6,%7}, {%8,%9,%10,%11}, %12, p, 1, 1, 1;}"
                 : R8(d, 0) : "r"(a[0]), "r"(a[1]), "r"(a[2]), "r"(a[3]), "l"(db));
}
__device__ __forceinline__ void q_gemm(float* d, uint64_t da, uint64_t db) {
    asm volatile("{.reg .pred p, q; .reg .b64 a, b; setp.ne.b32 p, 0, 0; setp.eq.b32 q, 0, 0;\n"
                 "wgmma.fence.sync.aligned;\n"
                 "wgmma.mma_async.sync.aligned.m64n96k16.f32.bf16.bf16 " L48 ", %48, %49, p, 1, 1, 1, 0;\n"
                 "add.s64 a, %48, 128; add.s64 b, %49, 2;\n"
                 "wgmma.mma_async.sync.aligned.m64n96k16.f32.bf16.bf16 " L48 ", a, b, q, 1, 1, 1, 0;\n"
                 "add.s64 a, %48, 256; add.s64 b, %49, 4;\n"
                 "wgmma.mma_async.sync.aligned.m64n96k16.f32.bf16.bf16 " L48 ", a, b, q, 1, 1, 1, 0;\n"
                 "add.s64 a, %48, 384; add.s64 b, %49, 6;\n"
                 "wgmma.mma_async.sync.aligned.m64n96k16.f32.bf16.bf16 " L48 ", a, b, q, 1, 1, 1, 0;\n"
                 "wgmma.commit_group.sync.aligned;\n"
                 "wgmma.wait_group.sync.aligned 0;}"
                 : W8(d, 0), W8(d, 8), W8(d, 16), W8(d, 24), W8(d, 32), W8(d, 40)
                 : "l"(da), "l"(db) : "memory");
}
__device__ __forceinline__ void ss64t(float* d, uint64_t da, uint64_t db, int acc) {
    asm volatile("{.reg .pred p; setp.ne.b32 p, %34, 0;\n"
                 "wgmma.mma_async.sync.aligned.m64n64k16.f32.bf16.bf16 " L32 ", %32, %33, p, 1, 1, 0, 1;}"
                 : R8(d, 0), R8(d, 8), R8(d, 16), R8(d, 24)
                 : "l"(da), "l"(db), "r"(acc));
}
template <int NREG> __device__ __forceinline__ void fence_regs(float* d) {
#pragma unroll
    for (int i = 0; i < NREG; i++) asm volatile("" : "+f"(d[i])::"memory");
}
template <int NREG> __device__ __forceinline__ void fence_regs(uint32_t* d) {
#pragma unroll
    for (int i = 0; i < NREG; i++) asm volatile("" : "+r"(d[i])::"memory");
}
__device__ __forceinline__ void ldsm4t(uint32_t* r, uint32_t addr) {
    asm volatile("ldmatrix.sync.aligned.m8n8.x4.trans.shared.b16 {%0,%1,%2,%3}, [%4];"
                 : "=r"(r[0]), "=r"(r[1]), "=r"(r[2]), "=r"(r[3]) : "r"(addr) : "memory");
}
__device__ __forceinline__ void stsm4t(uint32_t addr, uint32_t a, uint32_t b, uint32_t c, uint32_t d) {
    asm volatile("stmatrix.sync.aligned.m8n8.x4.trans.shared.b16 [%0], {%1,%2,%3,%4};" ::"r"(addr), "r"(a), "r"(b), "r"(c), "r"(d) : "memory");
}
__device__ __forceinline__ void cp16(uint32_t s, const void* g) {
    asm volatile("cp.async.cg.shared.global [%0], [%1], 16;" ::"r"(s), "l"(g) : "memory");
}
__device__ __forceinline__ void cp4(uint32_t s, const void* g) {
    asm volatile("cp.async.ca.shared.global [%0], [%1], 4;" ::"r"(s), "l"(g) : "memory");
}
__device__ __forceinline__ void cp16z(uint32_t s, const void* g, uint32_t skip) {
    asm volatile("{.reg .pred p; setp.ne.u32 p, %2, 0; cp.async.cg.shared.global [%0], [%1], 16, p;}" ::"r"(s), "l"(g), "r"(skip) : "memory");
}
__device__ __forceinline__ void cp_commit() { asm volatile("cp.async.commit_group;" ::: "memory"); }
template <int N> __device__ __forceinline__ void cp_wait() { asm volatile("cp.async.wait_group %0;" ::"n"(N) : "memory"); }
__device__ __forceinline__ void cp_wait_all() { asm volatile("cp.async.wait_all;" ::: "memory"); }
__device__ __forceinline__ void mbar_init(uint32_t a, int cnt) { asm volatile("mbarrier.init.shared::cta.b64 [%0], %1;" ::"r"(a), "r"(cnt) : "memory"); }
__device__ __forceinline__ void mbar_arrive(uint32_t a) { asm volatile("mbarrier.arrive.shared::cta.b64 _, [%0];" ::"r"(a) : "memory"); }
__device__ __forceinline__ void mbar_cp_arrive(uint32_t a) { asm volatile("cp.async.mbarrier.arrive.noinc.shared::cta.b64 [%0];" ::"r"(a) : "memory"); }
__device__ __forceinline__ void mbar_wait(uint32_t a, uint32_t parity) {
    asm volatile("{.reg .pred p; .reg .u32 n; mov.u32 n, 0;\n"
                 "MW_%=: mbarrier.try_wait.parity.shared::cta.b64 p, [%0], %1;\n"
                 "@p bra MD_%=;\n"
                 "add.u32 n, n, 1; setp.gt.u32 p, n, 0x100000;\n"
                 "@p trap;\n"
                 "bra MW_%=;\n"
                 "MD_%=: }" ::"r"(a), "r"(parity) : "memory");
}
template <int ID, int CNT> __device__ __forceinline__ void bar_sync()   { asm volatile("bar.sync %0, %1;" ::"n"(ID), "n"(CNT) : "memory"); }
template <int ID, int CNT> __device__ __forceinline__ void bar_arrive() { asm volatile("bar.arrive %0, %1;" ::"n"(ID), "n"(CNT) : "memory"); }
__device__ __forceinline__ float tanh_fast(float x) { float y; asm("tanh.approx.f32 %0, %1;" : "=f"(y) : "f"(x)); return y; }
__device__ __forceinline__ uint32_t pack2(float lo, float hi) {
    uint32_t r; asm("cvt.rn.bf16x2.f32 %0, %1, %2;" : "=r"(r) : "f"(hi), "f"(lo)); return r;
}
__device__ __forceinline__ uint32_t pack2h(float lo, float hi) {
    uint32_t r; asm("cvt.rn.f16x2.f32 %0, %1, %2;" : "=r"(r) : "f"(hi), "f"(lo)); return r;
}
__device__ __forceinline__ float bf_lo(uint32_t v) { return __uint_as_float(v << 16); }
__device__ __forceinline__ float bf_hi(uint32_t v) { return __uint_as_float(v & 0xFFFF0000u); }
__device__ __forceinline__ uint32_t bf2h(uint32_t v) { return pack2h(bf_lo(v), bf_hi(v)); }
__device__ __forceinline__ uint32_t amax2(uint32_t a, uint32_t b) {
    uint32_t r; asm("max.NaN.xorsign.abs.bf16x2 %0, %1, %2;" : "=r"(r) : "r"(a), "r"(b)); return r;
}
__device__ __forceinline__ uint32_t amax_fin(uint32_t m) { return max(m & 0x7FFFu, (m >> 16) & 0x7FFFu); }
__device__ __forceinline__ uint32_t silu_h2(uint32_t h) {
    uint32_t t, s;
    asm("tanh.approx.f16x2 %0, %1;" : "=r"(t) : "r"(h));
    asm("fma.rn.f16x2 %0, %1, %2, %1;" : "=r"(s) : "r"(h), "r"(t));
    return s;
}
__device__ __forceinline__ uint32_t hadd2(uint32_t a, uint32_t b) { uint32_t s; asm("add.rn.f16x2 %0, %1, %2;" : "=r"(s) : "r"(a), "r"(b)); return s; }
__device__ __forceinline__ uint32_t lds32(uint32_t a) { uint32_t v; asm volatile("ld.shared.b32 %0, [%1];" : "=r"(v) : "r"(a) : "memory"); return v; }
__device__ __forceinline__ uint32_t lds16(uint32_t a) { uint32_t v; asm volatile("ld.shared.u16 %0, [%1];" : "=r"(v) : "r"(a) : "memory"); return v; }
__device__ __forceinline__ uint4 lds128(uint32_t a) {
    uint4 v; asm volatile("ld.shared.v4.b32 {%0,%1,%2,%3}, [%4];" : "=r"(v.x), "=r"(v.y), "=r"(v.z), "=r"(v.w) : "r"(a) : "memory"); return v;
}
__device__ __forceinline__ void sts16(uint32_t a, uint32_t v) { asm volatile("st.shared.u16 [%0], %1;" ::"r"(a), "r"(v) : "memory"); }
__device__ __forceinline__ void sts32(uint32_t a, uint32_t v) { asm volatile("st.shared.b32 [%0], %1;" ::"r"(a), "r"(v) : "memory"); }
__device__ __forceinline__ void sts64(uint32_t a, uint32_t x, uint32_t y) { asm volatile("st.shared.v2.b32 [%0], {%1,%2};" ::"r"(a), "r"(x), "r"(y) : "memory"); }
__device__ __forceinline__ void sts128(uint32_t a, uint32_t x, uint32_t y, uint32_t z, uint32_t w) {
    asm volatile("st.shared.v4.b32 [%0], {%1,%2,%3,%4};" ::"r"(a), "r"(x), "r"(y), "r"(z), "r"(w) : "memory");
}
template <uint32_t V> __device__ __forceinline__ uint32_t atoms_add(uint32_t a) {
    uint32_t v; asm volatile("atom.shared.add.u32 %0, [%1], %2;" : "=r"(v) : "r"(a), "n"(V) : "memory"); return v;
}
__device__ __forceinline__ uint2 lds64(uint32_t a) {
    uint2 v; asm volatile("ld.shared.v2.b32 {%0,%1}, [%2];" : "=r"(v.x), "=r"(v.y) : "r"(a) : "memory"); return v;
}
__device__ __forceinline__ void st_rel64(void* p, uint32_t x, uint32_t y) {
    asm volatile("st.relaxed.gpu.global.b64 [%0], %1;" ::"l"(p), "l"((uint64_t)x | ((uint64_t)y << 32)) : "memory");
}
__device__ __forceinline__ uint64_t ld_rel64(const void* p) {
    uint64_t v; asm volatile("ld.relaxed.gpu.global.b64 %0, [%1];" : "=l"(v) : "l"(p) : "memory"); return v;
}
__device__ __forceinline__ uint32_t ld_acq32(const void* p) {
    uint32_t v; asm volatile("ld.acquire.gpu.global.b32 %0, [%1];" : "=r"(v) : "l"(p) : "memory"); return v;
}
__device__ __forceinline__ uint32_t ld_g32(const void* p) {
    uint32_t v; asm volatile("ld.global.b32 %0, [%1];" : "=r"(v) : "l"(p) : "memory"); return v;
}
__device__ __forceinline__ uint32_t ld_src(const void* p, uint32_t rec) {
    uint32_t v;
    asm volatile("{.reg .pred q; .reg .u64 a; .reg .u32 t; and.b32 t, %2, %3; setp.eq.u32 q, t, 0; and.b32 t, %2, 0xFFFFF; mad.wide.u32 a, t, 4, %1;\n"
                 "mov.b32 %0, %4; @q ld.global.nc.L1::no_allocate.b32 %0, [a];}" : "=&r"(v) : "l"(p), "r"(rec), "n"(PADW), "n"(NN) : "memory");
    return v;
}
__device__ __forceinline__ uint4 ld_row(const void* p, uint32_t n) {
    uint4 v;
    asm volatile("{.reg .pred q; .reg .u64 a; setp.lt.u32 q, %5, %6; mad.wide.u32 a, %5, 128, %4;\n"
                 "mov.b32 %0, 0; mov.b32 %1, 0; mov.b32 %2, 0; mov.b32 %3, 0;\n"
                 "@q ld.global.L1::no_allocate.v4.b32 {%0,%1,%2,%3}, [a];}"
                 : "=&r"(v.x), "=&r"(v.y), "=&r"(v.z), "=&r"(v.w) : "l"(p), "r"(n), "n"(NN) : "memory");
    return v;
}
__device__ __forceinline__ uint4 ld_stream(const void* p) {
    uint4 v;
    asm volatile("ld.global.nc.L1::no_allocate.v4.b32 {%0,%1,%2,%3}, [%4];" : "=r"(v.x), "=r"(v.y), "=r"(v.z), "=r"(v.w) : "l"(p) : "memory");
    return v;
}
__device__ __forceinline__ uint32_t atoms_addr(uint32_t a, uint32_t inc) {
    uint32_t v; asm volatile("atom.shared.add.u32 %0, [%1], %2;" : "=r"(v) : "r"(a), "r"(inc) : "memory"); return v;
}
template <uint32_t LIM, uint32_t BIT> __device__ __forceinline__ void put(uint32_t v, uint32_t w, uint32_t& mask) {
    asm volatile("{.reg .pred q, o; .reg .u32 t; setp.lt.u32 q|o, %1, %3; and.b32 t, %1, 0x3FFFF;\n"
                 "@q st.shared.b32 [t], %2; @o or.b32 %0, %0, %4;}" : "+r"(mask) : "r"(v), "r"(w), "n"(LIM), "n"(BIT) : "memory");
}
template <uint32_t LIM> __device__ __forceinline__ void put(uint32_t v, uint32_t w) {
    asm volatile("{.reg .pred q; .reg .u32 t; setp.lt.u32 q, %0, %2; and.b32 t, %0, 0x3FFFF; @q st.shared.b32 [t], %1;}"
                 ::"r"(v), "r"(w), "n"(LIM) : "memory");
}
__device__ __forceinline__ uint4 ld_rec(const uint4* p) {
    uint4 v;
    asm volatile("ld.relaxed.gpu.global.v4.b32 {%0,%1,%2,%3}, [%4];" : "=r"(v.x), "=r"(v.y), "=r"(v.z), "=r"(v.w) : "l"(p) : "memory");
    return v;
}
__device__ __forceinline__ void bulk_store(void* g, uint32_t s, uint32_t bytes) {
    asm volatile("cp.async.bulk.global.shared::cta.bulk_group [%0], [%1], %2;\n"
                 "cp.async.bulk.commit_group;" ::"l"(g), "r"(s), "r"(bytes) : "memory");
}
__device__ __forceinline__ void bulk_wait()      { asm volatile("cp.async.bulk.wait_group 0;" ::: "memory"); }
__device__ __forceinline__ void bulk_wait_read() { asm volatile("cp.async.bulk.wait_group.read 0;" ::: "memory"); }
__device__ __forceinline__ void l2_prefetch(const void* p, uint32_t bytes) {
    asm volatile("cp.async.bulk.prefetch.L2.global [%0], %1;" ::"l"(p), "r"(bytes) : "memory");
}
__device__ __forceinline__ const char* madw(uint32_t a, uint32_t b, const char* p) {
    const char* r; asm("mad.wide.u32 %0, %1, %2, %3;" : "=l"(r) : "r"(a), "r"(b), "l"(p)); return r;
}
__device__ __forceinline__ uint64_t dsc(uint32_t lo, uint32_t hi) { return (uint64_t)lo | ((uint64_t)hi << 32); }
__device__ __forceinline__ uint32_t dlo(uint32_t addr) { return ((addr & 0x3FFFF) >> 4) | 0x10000u; }
constexpr uint32_t DH128 = (1024 >> 4) | (1u << 30), DH32A = (512 >> 4) | (3u << 30), DH32B = (256 >> 4) | (3u << 30);
__device__ __forceinline__ bool elect() {
    uint32_t r;
    asm volatile("{.reg .pred p; elect.sync _|p, 0xFFFFFFFF; selp.u32 %0, 1, 0, p;}" : "=r"(r));
    return r != 0;
}
__device__ __forceinline__ int node2row(int n) { return ((n >> 3) & 1) * 96 + (n >> 4) * 8 + (n & 7); }
__device__ __forceinline__ int row2node(int r) { return r < 96 ? (r >> 3) * 16 + (r & 7) : ((r - 96) >> 3) * 16 + 8 + (r & 7); }
__device__ __forceinline__ int col2pos(int c) { return (c & ~15) | ((c & 7) << 1) | ((c >> 3) & 1); }

struct Args {
    uint32_t* ctl;
    const int* dst;
    uint4* ra;
    const __nv_bfloat16 *x, *w1, *b1;
    const int* src;
    const __nv_bfloat16 *ea, *w2, *b2;
    __nv_bfloat16* out;
    uint4* xh;
    uint2* rx;
};

__device__ __forceinline__ void bin_overflow(uint32_t sb, uint32_t rec, uint32_t v) {
    const uint32_t ix = atoms_add<1>(sb + F_XC);
    if (ix < OVC) sts64(sb + SM_OVL + ix * 8, rec, v);
    else sts32(sb + F_BAD, 1u);
}
__device__ __forceinline__ void send_extra(uint32_t sb, uint32_t mask, uint32_t ep, const Args& a) {
#pragma unroll 1
    while (mask) {
        const uint32_t i = __ffs(mask) - 1, off = threadIdx.x * 4 + (3 - (i >> 2)) * 2048 + (i & 3);
        mask &= mask - 1;
        const uint32_t d = a.dst[blockIdx.x * CH + off], b = __umulhi(d, 22605092u);
        const uint32_t ix = atoms_add<1>(sb + SM_STA + (b + (b < blockIdx.x ? G : 0) - blockIdx.x) * RP + RS * 4) & 0x1FFFu;
        if (ix < RX) st_rel64(a.rx + (b * G + blockIdx.x) * RX + ix, ((d - b * NPB) << 24) + off, ep);
    }
}
template <int MODE> __device__ __forceinline__ void recv_extra(uint32_t sb, uint32_t n, uint32_t run, uint32_t ep, const Args& a) {
    if (n > RX) { sts32(sb + F_BAD, 1u); n = 0; }
    const uint2* p = a.rx + (blockIdx.x * G + run) * RX;
#pragma unroll 1
    for (uint32_t i = 0; i < n; i++) {
        uint64_t w = ld_rel64(p + i);
        int it = 0;
        while (MODE == 3 && (uint32_t)(w >> 32) != ep) {
            if (++it > (1 << 22)) __trap();
            w = ld_rel64(p + i);
        }
        const uint32_t rec = (uint32_t)w + run * CH, v = atoms_add<CINC>(sb + SM_DEG + (rec >> 24) * 4);
        if (v < BINL) sts32(v & 0x3FFFFu, rec);
        else bin_overflow(sb, rec, v);
    }
}
__device__ __forceinline__ void load_w2(uint32_t sb, int u, int nthr, const Args& a) {
    for (int i = u; i < 128 * 32; i += nthr) {
        const int kp = i >> 5, w = i & 31;
        const int k = (kp & ~15) | ((kp & 1) << 3) | ((kp >> 1) & 7);
        cp4(sb + SM_W2 + kp * 128 + (((w & 7) ^ (kp & 7)) << 4) + (w >> 3) * 4, a.w2 + k * 64 + w * 2);
    }
    if (u < 8) cp16(sb + SM_B2 + u * 16, a.b2 + u * 8);
    cp_wait_all();
}

template <int FAST> __device__ __forceinline__ void tail_gemm(uint32_t sb, int wg, int warp4, int lane, int bucket, __nv_bfloat16* __restrict__ out) {
    const int g = lane >> 2, q = lane & 3;
    float d[32];
#pragma unroll
    for (int i = 0; i < 32; i++) d[i] = 0.f;
    wg_fence();
#pragma unroll
    for (int ks = 0; ks < 8; ks++)
        ss64t(d, mkdesc(sb + SM_QA + (ks >> 2) * 24576 + wg * 8192 + (ks & 3) * 32, 16, 1024, 1),
              mkdesc(sb + SM_W2 + ks * 2048, 16, 1024, 1), ks);
    wg_commit();
    const uint4 bb0 = lds128(sb + SM_B2 + q * 32), bb1 = lds128(sb + SM_B2 + q * 32 + 16);
    const int node0 = row2node(wg * 64 + warp4 * 16 + g);
    const uint32_t dg0 = (lds32(sb + SM_DEG + node0 * 4) >> (18 * FAST)) - FAST, dg1 = (lds32(sb + SM_DEG + node0 * 4 + 64) >> (18 * FAST)) - FAST;
    wg_wait<0>();
    fence_regs<32>(d);
    const uint32_t bw[8] = {bb0.x, bb0.y, bb0.z, bb0.w, bb1.x, bb1.y, bb1.z, bb1.w};
    uint32_t m = 0;
#pragma unroll
    for (int r = 0; r < 2; r++) {
        const int node = node0 + 16 * r;
        const int gn = bucket * NPB + node;
        const uint32_t dg = r ? dg1 : dg0;
        const float fd = (float)dg;
        uint32_t o[8];
#pragma unroll
        for (int j = 0; j < 8; j++) {
            const float v0 = fmaf(fd, bf_lo(bw[j]), d[4 * j + 2 * r]);
            const float v1 = fmaf(fd, bf_hi(bw[j]), d[4 * j + 2 * r + 1]);
            o[j] = dg ? pack2(v0, v1) : 0u;
            m = amax2(m, o[j]);
        }
        if (node < NPB && gn < NN) {
            uint4* op = reinterpret_cast<uint4*>(out + (size_t)gn * 64 + 16 * q);
            op[0] = make_uint4(o[0], o[1], o[2], o[3]);
            op[1] = make_uint4(o[4], o[5], o[6], o[7]);
        }
    }
    if (amax_fin(m) >= 0x7F80u) sts32(sb + F_NF, 1u);
}
__device__ __forceinline__ void tail_scan(uint32_t sb, int u) {
    uint32_t m = 0;
#pragma unroll
    for (int j = 0; j < 6; j++) {
        const int row = (u >> 3) + 32 * j;
        const uint32_t dg = lds32(sb + SM_DEG + row2node(row) * 4) >> 19;
        const uint4 a = lds128(sb + SM_QA + row * 128 + (u & 7) * 16), b = lds128(sb + SM_QA + 24576 + row * 128 + (u & 7) * 16);
        const uint32_t v = amax2(amax2(amax2(a.x, a.y), amax2(a.z, a.w)), amax2(amax2(b.x, b.y), amax2(b.z, b.w)));
        if (dg) m = amax2(m, v);
    }
    const float thr = (float)lds32(sb + F_DMAX) * (1.f / 32768.f) * fmaf(88.f, bf_lo(lds32(sb + F_WMAX)), 30.f);
    if (bf_lo(amax_fin(m)) >= thr) sts32(sb + F_BIG, 1u);
}
__device__ __forceinline__ bool tail_failed(uint32_t sb) {
    bar_sync<1, NT>();
    return lds32(sb + F_NF) != 0 || lds32(sb + F_BIG) == 0;
}

__device__ __forceinline__ void slow_path(uint32_t sb, int bucket, const Args& a) {
    const int tid = threadIdx.x, lane = tid & 31, j = tid & 127, wg = tid >> 7;
    bar_sync<0, NT>();
    for (int i = tid; i < NPB * 128; i += NT) sts32(sb + SM_SAGG + i * 4, 0u);
    if (tid < 192) sts32(sb + SM_DEG + tid * 4, 0u);
    const unsigned short* w1u = reinterpret_cast<const unsigned short*>(a.w1);
    {
        uint32_t w[32];
#pragma unroll
        for (int k = 0; k < 32; k++) w[k] = w1u[(64 + 2 * k) * 128 + j] | ((uint32_t)w1u[(65 + 2 * k) * 128 + j] << 16);
        const float bj = __bfloat162float(a.b1[j]);
        for (int node = wg; node < NPB && bucket * NPB + node < NN; node += 5) {
            const uint4* xr = reinterpret_cast<const uint4*>(a.x + (size_t)(bucket * NPB + node) * 64);
            float h = bj;
            fence_regs<32>(w);
#pragma unroll
            for (int k = 0; k < 8; k++) {
                const uint4 v = __ldg(xr + k);
                const uint32_t vv[4] = {v.x, v.y, v.z, v.w};
#pragma unroll
                for (int i = 0; i < 4; i++) {
                    h = fmaf(bf_lo(vv[i]), bf_lo(w[4 * k + i]), h);
                    h = fmaf(bf_hi(vv[i]), bf_hi(w[4 * k + i]), h);
                }
            }
            sts32(sb + SM_SQ + (node * 128 + j) * 4, __float_as_uint(h));
        }
    }
    uint32_t w[40];
#pragma unroll
    for (int k = 0; k < 40; k++) {
        const int r = k < 32 ? 2 * k : 2 * k + 64;
        w[k] = w1u[r * 128 + j] | ((uint32_t)w1u[(r + 1) * 128 + j] << 16);
    }
    bar_sync<0, NT>();
    for (int e0 = wg * 32; e0 < NE; e0 += 160) {
        const int dn = a.dst[e0 + lane] - bucket * NPB;
        unsigned m = __ballot_sync(0xFFFFFFFFu, dn >= 0 && dn < NPB);
        while (m) {
            const int l = __ffs(m) - 1;
            m &= m - 1;
            const int node = __shfl_sync(0xFFFFFFFFu, dn, l);
            const int e = e0 + l;
            const uint4* xr = reinterpret_cast<const uint4*>(a.x + (size_t)a.src[e] * 64);
            const uint4* er = reinterpret_cast<const uint4*>(a.ea + (size_t)e * 16);
            float h = __uint_as_float(lds32(sb + SM_SQ + (node * 128 + j) * 4));
            fence_regs<40>(w);
#pragma unroll
            for (int k = 0; k < 10; k++) {
                const uint4 v = (k < 8) ? __ldg(xr + k) : __ldg(er + (k - 8));
                const uint32_t vv[4] = {v.x, v.y, v.z, v.w};
#pragma unroll
                for (int i = 0; i < 4; i++) {
                    h = fmaf(bf_lo(vv[i]), bf_lo(w[4 * k + i]), h);
                    h = fmaf(bf_hi(vv[i]), bf_hi(w[4 * k + i]), h);
                }
            }
            h *= 0.5f;
            const float f = fmaf(h, tanh_fast(h), h);
            asm volatile("red.shared.add.f32 [%0], %1;" ::"r"(sb + SM_SAGG + (node * 128 + j) * 4), "f"(f) : "memory");
            if (j == 0) atoms_add<1>(sb + SM_DEG + node * 4);
        }
    }
    bar_sync<0, NT>();
    load_w2(sb, tid, NT, a);
    for (int i = tid; i < NPB * 64; i += NT) {
        const int node = i >> 6, pr = i & 63;
        const int hid = (pr >> 3) * 16 + (pr & 7);
        const float u = __uint_as_float(lds32(sb + SM_SAGG + (node * 128 + hid) * 4));
        const float v = __uint_as_float(lds32(sb + SM_SAGG + (node * 128 + hid + 8) * 4));
        const int ch = (pr & 31) >> 2;
        sts32(sb + SM_QA + (pr >> 5) * 24576 + node2row(node) * 128 + ((ch ^ (node & 7)) << 4) + (pr & 3) * 4, pack2(u, v));
    }
    fence_async();
    bar_sync<0, NT>();
    if (wg < 3) tail_gemm<0>(sb, wg, (tid >> 5) & 3, lane, bucket, a.out);
}

template <int MODE>
__device__ __forceinline__ bool producer(uint32_t sb, const Args& a) {
    const int tid = threadIdx.x, lane = tid & 31, warp = tid >> 5, warp4 = warp & 3, u = tid - 512;
    const int cta = blockIdx.x;
    const int nrow = min(NPB, NN - cta * NPB);
    asm volatile("setmaxnreg.dec.sync.aligned.u32 64;");
    const uint32_t ep = MODE == 3 ? ld_g32(a.ctl + 32 + 32 * cta) + 1 : 0;
    auto load_w1 = [&](int j0, int j1) {
        const int r = u >> 4, c = u & 15;
        const uint32_t sw = r * 128 + (((c & 7) ^ r) << 4);
        const __nv_bfloat16* wp = a.w1 + u * 8;
#pragma unroll
        for (int j = j0; j < j1; j++) {
            const uint32_t d = j < 8 ? SM_W1A + j * 1024 : j < 16 ? SM_W1B + (j - 8) * 1024 : SM_W1A + (j - 8) * 1024;
            cp16(sb + d + (c >> 3) * (j < 8 || j >= 16 ? 10240 : 8192) + sw, wp + j * 1024);
        }
    };
    if (MODE & 2) {
        if (u == 32) {
#pragma unroll
            for (int i = 0; i < 4; i++) {
                mbar_init(sb + SM_BAR + i * 8, 128 + 4);
                mbar_init(sb + SM_BAR + 32 + i * 8, 8);
            }
            mbar_init(sb + B_X, 128);
        }
        if (u == 64 && cta == G - 1) { l2_prefetch(a.w2, 16384); l2_prefetch(a.b2, 128); }
        __syncwarp();
    }
    bar_sync<9, 160>();
    {
        const int xrow = u >> 3;
        const uint32_t xa = sb + SM_XO + xrow * 128 + (((u & 7) ^ (xrow & 7)) << 4);
        const __nv_bfloat16* xp = a.x + (size_t)cta * NPB * 64 + (u & 7) * 8;
#pragma unroll
        for (int j = 0; j < 12; j++) cp16z(xa + j * 2048, xp + min(xrow + 16 * j, nrow - 1) * 64, xrow + 16 * j >= nrow);
        cp_commit();
        if (MODE & 2) {
            load_w1(0, 18);
            if (u < 16) cp16(sb + SM_B1 + u * 16, a.b1 + u * 8);
            mbar_cp_arrive(sb + B_X);
        }
        cp_commit();
        cp_wait<1>();
        CSTAMP(20, u == 0);
        if ((MODE & 2) && u == 0) l2_prefetch(a.src + cta * CH, min(CH, NE - cta * CH) * 4);
        __syncwarp();
        if (MODE & 1) {
#pragma unroll
            for (int j0 = 0; j0 < 12; j0 += 6) {
                uint4 v[6];
#pragma unroll
                for (int j = 0; j < 6; j++) v[j] = lds128(xa + (j0 + j) * 2048);
#pragma unroll
                for (int j = 0; j < 6; j++) sts128(sb + SM_XR + u * 16 + (j0 + j) * 2048, bf2h(v[j].x), bf2h(v[j].y), bf2h(v[j].z), bf2h(v[j].w));
            }
            fence_async();
            if (warp4 != 3) bar_arrive<4, MODE == 3 ? 160 : 128>();
        }
        if (MODE & 2) {
            mbar_wait(sb + B_X, 0);
            if (u < 80) {
                uint32_t m = 0;
#pragma unroll
                for (int c = 0; c < 16; c++) {
                    const uint4 v = lds128(sb + SM_W1A + (c >> 3) * 10240 + u * 128 + (((c & 7) ^ (u & 7)) << 4));
                    m = amax2(m, amax2(amax2(v.x, v.y), amax2(v.z, v.w)));
                }
                m = amax_fin(m);
                if (m != 0 && m < 0x3A00u) sts32(sb + F_BAD, 1u);
                asm volatile("red.shared.max.u32 [%0], %1;" ::"r"(sb + F_WMAX), "r"(m) : "memory");
            }
            __syncwarp();
            bar_arrive<3, NT>();
        }
        if ((MODE & 1) && warp4 == 3) {
            bar_sync<4, MODE == 3 ? 160 : 128>();
            if (lane == 0) {
                const int nr = min(NPB, NN + 1 - cta * NPB);
                uint32_t t0 = clock();
#pragma unroll 1
                for (int r = 0; r < nr; r += PROWS) {
                    bulk_store(a.xh + ((size_t)cta * NPB + r) * 8, sb + SM_XR + r * 128, min(PROWS, nr - r) * 128);
                    while (MODE == 3 && (uint32_t)clock() - t0 < PDT) {}
                    t0 += PDT;
                }
                bulk_wait();
                CSTAMP(14, true);
                if (MODE == 3) {
                    asm volatile("red.release.gpu.global.add.u32 [%0], 1;" ::"l"(a.ctl) : "memory");
                    a.ctl[32 + 32 * cta] = ep;
                    CSTAMP(16, true);
                    int it = 0;
                    while ((int)(ld_acq32(a.ctl) - ep * G) < 0)
                        if (++it > (1 << 22)) __trap();
                    CSTAMP(13, true);
                }
            }
            __syncwarp();
        }
    }
    if (!(MODE & 2)) return false;
    const char* xb = reinterpret_cast<const char*>(a.xh) + (lane & 7) * 16;
    const char* eb = reinterpret_cast<const char*>(a.ea) + (lane & 1) * 16;
    const char* sp = reinterpret_cast<const char*>(a.src);
    const int oc = warp4 * 32 + lane;
    const uint32_t posa = sb + SM_POS + col2pos(oc) * 2;
    auto lookup = [&](int t) { return lds32(sb + SM_BIN + lds16(posa + t * 256)); };
    const uint32_t raw = sb + SM_RAW + u * 16, sring = sb + SM_SR + oc * 4;
    auto fetch_s = [&](int slot, uint32_t rec) {
        if (rec & PADW) sts32(sring + slot * 512, NN);
        else cp4(sring + slot * 512, madw(rec & 0xFFFFFu, 4u, sp));
    };
    auto fetch_e = [&](int slot, uint32_t rec) {
        const uint32_t l0 = __shfl_sync(0xFFFFFFFFu, rec, lane >> 1), l1 = __shfl_sync(0xFFFFFFFFu, rec, 16 + (lane >> 1));
        cp16z(raw + slot * 4096, madw(l0 & 0xFFFFFu, 32u, eb), l0 & PADW);
        cp16z(raw + slot * 4096 + 2048, madw(l1 & 0xFFFFFu, 32u, eb), l1 & PADW);
    };
    auto fetch = [&](int slot, uint32_t rec) { fetch_s(slot, rec); fetch_e(slot, rec); };
    const int xc0 = warp4 * 32 + (lane >> 4) * 16 + ((lane >> 3) & 1) * 4;
    const uint32_t slist = sb + SM_SR + xc0 * 4;
    uint32_t xoff[4];
#pragma unroll
    for (int i = 0; i < 4; i++) xoff[i] = sb + SM_XE + (xc0 + i) * 128 + (((lane & 7) ^ ((xc0 + i) & 7)) << 4);
    const int ec = warp4 * 32 + (lane >> 1);
    const uint32_t eoff = sb + SM_XE + 16384 + ec * 32 + (((lane & 1) ^ ((ec >> 2) & 1)) << 4);
    const uint32_t ioff = sb + SM_IND + oc * 32 + (((oc >> 2) & 1) << 4);
    auto put_x = [&](const uint4& la, const uint4& lb, uint32_t so) {
        const uint32_t lw[8] = {la.x, la.y, la.z, la.w, lb.x, lb.y, lb.z, lb.w};
#pragma unroll
        for (int i = 0; i < 4; i++) {
            cp16(xoff[i] + so, madw(lw[i], 128u, xb));
            cp16(xoff[i] + so + 1024, madw(lw[4 + i], 128u, xb));
        }
        cp_commit();
    };
    auto put_e = [&](const uint32_t* ef, uint32_t cur, uint32_t so, uint32_t ia) {
        sts128(eoff + so, ef[0], ef[1], ef[2], ef[3]);
        sts128(eoff + so + 512, ef[4], ef[5], ef[6], ef[7]);
        sts128(ia, 0u, 0u, 0u, 0u);
        sts128(ia ^ 16, 0u, 0u, 0u, 0u);
        if (!(cur & PADW)) sts16(ia ^ ((cur >> 23) & 30u), 0x3C00u);
    };
    auto publish = [&](uint32_t bar, uint32_t cnt) {
        fence_async();
        __syncwarp();
        if (lane == 0) asm volatile("mbarrier.arrive.shared::cta.b64 _, [%0], %1;" ::"r"(bar), "r"(cnt) : "memory");
    };
    asm volatile("" : "+l"(xb), "+l"(eb), "+l"(sp));
    __syncwarp();
    bar_sync<5, NT>();
    const uint4 fl = lds128(sb + F_TOT);
    const uint32_t p0 = lds16(posa), p1 = lds16(posa + 256);
    const int T = fl.z ? 0 : ((int)fl.x + 63) >> 6;
    CSTAMP(17, u == 0 && T >= 0);
    const int T0 = (T + 1) >> 1, T1 = T >> 1;
    uint32_t own[4] = {PADW, PADW, PADW, PADW};
    if (T > 0) own[0] = lds32(sb + SM_BIN + p0);
    if (T > 1) own[1] = lookup(T - 1);
    if (T > 2) own[2] = lds32(sb + SM_BIN + p1);
    if (T > 3) own[3] = lookup(T - 2);
    fetch_e(0, own[0]);
    cp_commit();
    fetch_e(1, own[1]);
    cp_commit();
    CSTAMP(18, u == 0);
    uint32_t r2 = PADW, pc = lds16(posa + max(T - 3, 0) * 256);
    if (T > 4) r2 = lookup(2);
    auto first = [&](int s) {
        const uint4 e0 = lds128(raw + s * 4096), e1 = lds128(raw + s * 4096 + 2048);
        const uint32_t ef[8] = {bf2h(e0.x), bf2h(e0.y), bf2h(e0.z), bf2h(e0.w), bf2h(e1.x), bf2h(e1.y), bf2h(e1.z), bf2h(e1.w)};
        if (s < T) put_e(ef, own[s], s * XE_S, ioff + s * 4096);
        __syncwarp();
        if (lane == 0) mbar_arrive(sb + SM_BAR + s * 16);
    };
    cp_wait<1>();
    CSTAMP(21, u == 0);
    first(0);
    cp_wait<0>();
    first(1);
    CSTAMP(44, u == 0);
    bar_sync<6, NT>();
    if (lds32(sb + F_BAD)) {
        asm volatile("setmaxnreg.inc.sync.aligned.u32 96;");
        return true;
    }
    CSTAMP(45, u == 0);
    if (FP == 1 && T > 0) mbar_wait(sb + SM_BAR, 0);
    fetch(2, own[2]);
    cp_commit();
    if (FP == 2 && T > 0) mbar_wait(sb + SM_BAR, 0);
    fetch(3, own[3]);
    cp_commit();
    cp_commit();
    CSTAMP(26, u == 0);
    int i3 = 8192;
    uint32_t pb = 0, r0 = own[2], r1 = own[3];
    for (int k = 1; k < T0; k++) {
#pragma unroll
        for (int s = 0; s < 2; s++) {
            if (s == 1 && k >= T1) break;
            const int st = 2 * s + (k & 1), slot = 2 * (k & 1) + s;
            cp_wait<2>();
            __syncwarp();
            const uint4 e0 = lds128(raw + slot * 4096), e1 = lds128(raw + slot * 4096 + 2048);
            const uint4 la = lds128(slist + slot * 512), lb = lds128(slist + slot * 512 + 32);
            const uint32_t l0 = __shfl_sync(0xFFFFFFFFu, r2, lane >> 1), l1 = __shfl_sync(0xFFFFFFFFu, r2, 16 + (lane >> 1));
            const uint32_t r3 = lds32(sb + SM_BIN + pc);
            pc = lds16(posa + (s ? max(T - 3 - k, 0) : min(k + 2, T - 1)) * 256);
            const uint32_t ef[8] = {bf2h(e0.x), bf2h(e0.y), bf2h(e0.z), bf2h(e0.w), bf2h(e1.x), bf2h(e1.y), bf2h(e1.z), bf2h(e1.w)};
            const uint32_t ia = ioff + i3 + s * 4096;
            const uint32_t so = s * XE_S + (k & 1) * XE_P;
            mbar_wait(sb + SM_BAR + 32 + st * 8, ((k >> 1) & 1) ^ 1);
            CSTAMPV(26 + 2 * k + s, u == 0 && k <= 8);
            if (pb) {
                cp_wait<1>();
                publish(pb, 33);
            }
            pb = sb + SM_BAR + st * 8;
            put_x(la, lb, so);
            if (k < KF) mbar_cp_arrive(pb);
            put_e(ef, r0, so, ia);
            if (k < KF) {
                __syncwarp();
                if (lane == 0) mbar_arrive(pb);
                pb = 0;
            }
            if (k + 1 < (s ? T1 : T0)) {
                fetch_s(slot ^ 2, r2);
                cp16z(raw + (slot ^ 2) * 4096, madw(l0 & 0xFFFFFu, 32u, eb), l0 & PADW);
                cp16z(raw + (slot ^ 2) * 4096 + 2048, madw(l1 & 0xFFFFFu, 32u, eb), l1 & PADW);
            }
            cp_commit();
            r0 = r1;
            r1 = r2;
            r2 = r3;
        }
        i3 = (i3 == 16384) ? 0 : i3 + 8192;
    }
    cp_wait_all();
    if (pb) publish(pb, 33);
    bar_sync<10, 128>();
    load_w2(sb, u, 128, a);
    fence_async();
    bar_sync<1, NT>();
    tail_scan(sb, u + 128);
    if (!tail_failed(sb) || T == 0) return false;
    asm volatile("setmaxnreg.inc.sync.aligned.u32 96;");
    return true;
}

template <int MODE>
__device__ __forceinline__ bool consumer(uint32_t sb, const Args& a) {
    const int tid = threadIdx.x, lane = tid & 31, warp = tid >> 5, wg = tid >> 7, warp4 = warp & 3;
    const int cta = blockIdx.x;
    uint32_t ep = 1;
    {
        const int nv = min(CH, NE - cta * CH) >> 2;
        uint4 dv[3];
        if (MODE == 3) ep = ld_g32(a.ctl + 32 + 32 * cta);
        if (MODE & 1) {
            const int* dp = a.dst + cta * CH + tid * 4;
            dv[0] = ld_stream(dp);
            dv[1] = ld_stream(dp + 2048);
            dv[2] = ld_stream(tid + 1024 < nv ? dp + 4096 : dp);
        }
        if (tid >= 8 && tid < 16) sts32(sb + SM_FLAG + (tid - 8) * 4, 0u);
        if (tid == 16) sts32(sb + SM_BIN + PADO, PADW);
        __syncwarp();
        if ((XAT < 0 || !(MODE & 1)) && warp == 0) bar_sync<9, 160>();
        if (tid >= 64 && tid < 288)
            sts32(sb + SM_DEG + (tid - 64) * 4, tid >= 256 ? 0xC0000000u : (1u << 18) + sb + SM_BIN + (tid - 64 < NPB ? (tid - 64) * BINP : PADO));
        else if (tid >= 288 && tid < 288 + G) sts32(sb + SM_CNT + (tid - 288) * 4, sb + SM_STA + (tid - 288 + (tid - 288 < cta ? G : 0) - cta) * RP);
        if (MODE == 3) ep++;
        const uint32_t tg = ((ep & 255u) + 256u) << 13;
        if (MODE & 1) {
            const uint32_t pw = tg + 0xC0000000u + (lane << 24);
#pragma unroll
            for (int j = 0; j < 5; j++)
                if (tid + 512 * j < G * RU) sts128(sb + SM_STA + tid * 16 + j * 8192, pw, pw, pw, pw);
        }
        CSTAMP(22, tid == 0);
        bar_sync<2, 512>();
        if (MODE & 1) {
            uint32_t mask = 0, inc = CINC;
            asm volatile("" : "+r"(inc));
#pragma unroll
            for (int j = 0; j < 3; j++)
                if (j < 2 || tid + 1024 < nv) {
                    const uint32_t dd[4] = {dv[j].x, dv[j].y, dv[j].z, dv[j].w};
                    uint32_t w[4], pa[4];
#pragma unroll
                    for (int k = 0; k < 4; k++) {
                        const uint32_t b = __umulhi(dd[k], 22605092u);
                        pa[k] = atoms_addr(sb + SM_CNT + b * 4, inc);
                        w[k] = (dd[k] << 24) + (tg + tid * 4 + j * 2048 + k) - b * ((uint32_t)NPB << 24);
                    }
                    if (j == XAT && warp == 0) bar_sync<9, 160>();
                    if (j == 0) CSTAMP(2, tid == 0);
                    put<RUNL, 1u>(pa[0], w[0], mask);
                    put<RUNL, 2u>(pa[1], w[1], mask);
                    put<RUNL, 4u>(pa[2], w[2], mask);
                    put<RUNL, 8u>(pa[3], w[3], mask);
                    mask <<= 4;
                }
            if (__builtin_expect(mask != 0, 0)) send_extra(sb, tid + 1024 < nv ? mask : mask << 4, ep, a);
            CSTAMP(3, tid == 0);
            fence_async();
            __syncwarp();
            bar_sync<2, 512>();
            if (tid == 0) {
                bulk_store(a.ra + (size_t)cta * (G * RU), sb + SM_STA, G * RP);
                if (MODE == 1) bulk_wait();
            }
            __syncwarp();
        }
    }
    if (!(MODE & 2)) return false;
    asm volatile("setmaxnreg.inc.sync.aligned.u32 104;");
    CSTAMP(4, tid == 0);
    const int s = wg >> 1, h = wg & 1;
    uint32_t w1f[5][4];
    mbar_wait(sb + B_X, 0);
    fence_async();
    {
        float d[48];
        const float ba = 0.5f * bf_lo(lds16(sb + SM_B1 + (h * 64 + warp4 * 16 + (lane >> 2)) * 2));
        const float bb = 0.5f * bf_lo(lds16(sb + SM_B1 + (h * 64 + warp4 * 16 + (lane >> 2)) * 2 + 16));
        q_gemm(d, mkdesc(sb + SM_W1B + h * 8192, 16, 1024, 1), mkdesc(sb + SM_XO + s * 12288, 16, 1024, 1));
        const uint32_t qa = sb + SM_QA + h * 24576 + (lane >> 4) * 12288 + s * 6144 + (lane & 7) * 128 +
                            (((2 * warp4 + ((lane >> 3) & 1)) ^ (lane & 7)) << 4);
#pragma unroll
        for (int j = 0; j < 6; j++) {
            const float* e = d + 8 * j;
            stsm4t(qa + j * 1024, pack2h(fmaf(e[0], 0.5f, ba), fmaf(e[1], 0.5f, ba)), pack2h(fmaf(e[2], 0.5f, bb), fmaf(e[3], 0.5f, bb)),
                   pack2h(fmaf(e[4], 0.5f, ba), fmaf(e[5], 0.5f, ba)), pack2h(fmaf(e[6], 0.5f, bb), fmaf(e[7], 0.5f, bb)));
        }
    }
    fence_async();
    CSTAMP(19, tid == 0);
    {
        const int kr = (lane & 7) + 8 * (lane >> 4), ch = 2 * warp4 + ((lane >> 3) & 1);
#pragma unroll
        for (int ks = 0; ks < 5; ks++) {
            ldsm4t(w1f[ks], sb + SM_W1A + h * 10240 + (16 * ks + kr) * 128 + ((ch ^ (kr & 7)) << 4));
#pragma unroll
            for (int i = 0; i < 4; i++) w1f[ks][i] = pack2h(0.5f * bf_lo(w1f[ks][i]), 0.5f * bf_hi(w1f[ks][i]));
        }
    }
    {
        const uint32_t tg = ((ep & 255u) + 256u) << 13, pw = tg + 0xC0000000u + (lane << 24);
        uint32_t inc = CINC, i = tid, run;
        asm volatile("" : "+r"(inc));
        auto unit = [&](uint32_t i) {
            const uint32_t r = __umulhi(i, 226050911u);
            run = cta - r + (r > cta ? G : 0);
            return a.ra + (run * (G * RU) + i);
        };
        const uint4* gn = unit(i);
        if (MODE == 3) {
            if (tid == 0) bulk_wait_read();
            __syncwarp();
            bar_sync<2, 512>();
        }
        if (MODE == 3 && PUBR < 0 && warp == 3) bar_arrive<4, 160>();
        CSTAMP(24, tid == 0);
        uint4 nx = ld_rec(gn);
#pragma unroll 1
        do {
            uint4 rv = nx, v;
            const uint4* ga = gn;
            const uint32_t from = run, c0 = run * CH - tg;
            gn = unit(min(i + 512, G * RU - 1));
            if (MODE == 3) {
                int it = 0;
                while (__builtin_expect(__any_sync(0xFFFFFFFFu, ((rv.x ^ tg) | (rv.y ^ tg) | (rv.z ^ tg) | (rv.w ^ tg)) & TAGM), 0)) {
                    if (++it > (1 << 22)) __trap();
                    rv = ld_rec(ga);
                }
            }
            if (i < 2048) nx = ld_rec(gn);
            CSTAMP(23, tid == 0 && i == 0);
            CSTAMP(25, tid == 0 && i == 2048);
            if (i >= G * RU) rv.x = rv.y = rv.z = rv.w = pw;
            v.x = atoms_addr(sb + SM_DEG + (rv.x >> 22), inc);
            v.y = atoms_addr(sb + SM_DEG + (rv.y >> 22), inc);
            v.z = atoms_addr(sb + SM_DEG + (rv.z >> 22), inc);
            v.w = atoms_addr(sb + SM_DEG + (rv.w >> 22), inc);
            const bool ext = (rv.w ^ pw) - 1u < 0x1FFFu;
            put<BINL>(v.x, rv.x + c0);
            put<BINL>(v.y, rv.y + c0);
            put<BINL>(v.z, rv.z + c0);
            put<BINL>(v.w, rv.w + c0);
            if (__builtin_expect(max(max((int)v.x, (int)v.y), max((int)v.z, (int)v.w)) >= (int)BINL || ext, 0)) {
                if ((int)v.x >= (int)BINL) bin_overflow(sb, rv.x + c0, v.x);
                if ((int)v.y >= (int)BINL) bin_overflow(sb, rv.y + c0, v.y);
                if ((int)v.z >= (int)BINL) bin_overflow(sb, rv.z + c0, v.z);
                if ((int)v.w >= (int)BINL) bin_overflow(sb, rv.w + c0, v.w);
                if (ext) recv_extra<MODE>(sb, rv.w & 0x1FFFu, from, ep, a);
            }
            __syncwarp();
            if (MODE == 3 && (i >> 5) == PUBR * 16 + 3) bar_arrive<4, 160>();
            i += 512;
        } while (i < 2560);
    }
    CSTAMP(7, tid == 0);
    bar_sync<3, NT>();
    int T;
    uint4 xv[4];
    {
        uint32_t c[6], tot = 0, bef = 0;
#pragma unroll
        for (int j = 0; j < 6; j++) c[j] = lds32(sb + SM_DEG + lane * 4 + j * 128) >> 19;
        const uint32_t own = lds32(sb + SM_DEG + min(warp * 12 + lane, 191) * 4);
        const uint32_t bad = lds32(sb + F_BAD), no = lds32(sb + F_XC);
        CSTAMP(6, tid == 0 && own != 1);
#pragma unroll
        for (int j = 0; j < 6; j++) {
            tot += c[j];
            if (lane + 32 * j < warp * 12) bef += c[j];
        }
        uint32_t inc = own >> 19;
#pragma unroll
        for (int o = 1; o < 16; o <<= 1) {
            const uint32_t w = __shfl_up_sync(0xFFFFFFFFu, inc, o);
            if (lane >= o) inc += w;
        }
        tot = __reduce_add_sync(0xFFFFFFFFu, tot);
        bef = __reduce_add_sync(0xFFFFFFFFu, bef);
        const uint32_t pk = ((bef + inc - (own >> 19)) << 16) + (own >> 18);
        T = (tot + 63) >> 6;
        if (bad == 0 && tot <= CAP / 2) {
            if (lane < 12 && own < BINL + (1u << 18)) sts32(own & 0x3FFFFu, PADW);
            const int l8 = lane & 7;
            const uint32_t val = ((warp * 12 + (lane >> 3)) * BINP + l8 * 8) * 0x10001u + 0x40000u;
#pragma unroll
            for (int r = 0; r < 3; r++) {
                const uint32_t e = __shfl_sync(0xFFFFFFFFu, pk, 4 * r + (lane >> 3));
                const uint32_t ad = sb + SM_POS + (e >> 16) * 4 + l8 * 4, lim = (e & 0xFFFFu) - 2 * l8;
#pragma unroll
                for (int i = 0; i < 3; i++)
                    if ((int)lim > 16 * i + 1) sts32(ad + 32 * i, val + (uint32_t)(r * 4 * BINP + 64 * i) * 0x10001u);
            }
            if (tid < 64 && tot + tid < T * 64) sts32(sb + SM_POS + (tot + tid) * 4, PADO * 0x10001u);
            if (no) {
                if (lane < 12 && own >= BINL && !(own & (1u << 18))) sts16(sb + SM_POS + (pk >> 16) * 4 + (pk & 0xFFFFu) * 2 - 2, PADO);
#pragma unroll 1
                for (uint32_t i = 0; i < no; i += 32) {
                    const uint2 o = lds64(sb + SM_OVL + min(i + lane, OVC - 1u) * 8);
                    const uint32_t n = (o.x >> 24) - warp * 12, e = __shfl_sync(0xFFFFFFFFu, pk, n);
                    if (i + lane < no && n < 12) sts16(sb + SM_POS + (e >> 16) * 4 + (o.y >> 18) * 2 - 2, OVLO + (i + lane) * 8);
                }
            }
        } else if (tid == 0) sts32(sb + F_BAD, 1u);
        if (tid == 0) sts32(sb + F_TOT, tot);
        __syncwarp();
        CSTAMP(8, tid == 0);
        bar_sync<5, NT>();
        {
            uint32_t sv[4] = {NN, NN, NN, NN};
            if (bad == 0 && tot <= CAP / 2 && s < T) {
                const uint2 po = lds64(sb + SM_POS + (s ? T - 1 : 0) * 256 + (warp & 7) * 32 + (lane >> 3) * 8);
                const uint32_t rec[4] = {lds32(sb + SM_BIN + (po.x & 0xFFFFu)), lds32(sb + SM_BIN + (po.x >> 16)),
                                         lds32(sb + SM_BIN + (po.y & 0xFFFFu)), lds32(sb + SM_BIN + (po.y >> 16))};
#pragma unroll
                for (int j = 0; j < 4; j++) sv[j] = ld_src(a.src, rec[j]);
            }
#pragma unroll
            for (int j = 0; j < 4; j++) xv[j] = ld_row(a.x + (lane & 7) * 8, sv[j]);
        }
        CSTAMP(5, tid == 64);
        if (tid < T && lds32(sb + F_BAD) == 0) {
            const int T0 = (T + 1) >> 1;
            const uint32_t first = lds32(sb + SM_BIN + lds16(sb + SM_POS + tid * 256)) >> 24;
            const uint32_t last = lds32(sb + SM_BIN + lds16(sb + SM_POS + min(tid * 64u + 63u, tot - 1) * 4)) >> 24;
            const uint32_t w = min(first >> 3, 22u), ta = sb + SM_TT + (tid < T0 ? tid : 32 + T - 1 - tid) * 16;
            sts32(ta + 4, dlo(sb + SM_QA + ((w + 1) >> 1) * 1024));
            sts32(ta + 8, ((12288 - (w & 1) * 1024) >> 4) | (1u << 30));
            sts32(ta, (tid < T0 ? first : last) * 64);
            if (tid == T0) {
                sts32(sb + SM_TT + T0 * 16, first * 64);
                sts32(sb + SM_TT + (32 + T - T0) * 16, first * 64);
            }
            if (T == 1) sts32(sb + SM_TT + 16, NPB * 64);
            if ((last >> 3) > w + 1) sts32(sb + F_BAD, 1u);
        }
        if (warp == 2) {
            const uint32_t m = __reduce_max_sync(0xFFFFFFFFu, max(max(max(c[0], c[1]), max(c[2], c[3])), max(c[4], c[5])));
            if (lane == 0) sts32(sb + F_DMAX, 2 * m);
        }
        __syncwarp();
    }
    bar_arrive<6, NT>();
    bar_sync<2, 512>();
    if (lds32(sb + F_BAD)) {
        asm volatile("setmaxnreg.dec.sync.aligned.u32 96;");
        return true;
    }

    {
        const int wgu = __shfl_sync(0xFFFFFFFFu, wg, 0), Tu = __shfl_sync(0xFFFFFFFFu, T, 0);
        const int su = wgu >> 1, hu = wgu & 1;
        const int Ts = su ? Tu >> 1 : (Tu + 1) >> 1;
        if (Ts > 0) {
            const int q = lane & 3;
            const uint32_t a0 = q * 256 + (((2 * warp4 + (lane >> 4)) ^ (2 * q)) << 4) + ((lane >> 2) & 3) * 4, a1 = (a0 + 128) ^ 16;
            const uint32_t c0 = sb + SM_QA + hu * 24576 + (su ? 0 : 960) - 128 * q;
            uint32_t acc[32], pk[16], fa[4];
            float agg[8];
#pragma unroll
            for (int i = 0; i < 8; i++) agg[i] = 0.f;
#pragma unroll
            for (int i = 0; i < 16; i++) pk[i] = 0u;
            auto flush = [&](uint32_t F, bool on) {
                const uint32_t v = F + c0;
#pragma unroll
                for (int j = 0; j < 4; j++) {
                    const int i0 = (j >> 1) * 4 + (j & 1);
                    const uint32_t t = v - 64 * (j & 1) - 512 * (j >> 1);
                    if (on && ((t ^ fa[j]) & ~1023u)) {
                        sts32(fa[j] + (j >> 1) * 12288, pack2(agg[i0], agg[i0 + 2]));
                        agg[i0] = 0.f;
                        agg[i0 + 2] = 0.f;
                    }
                    asm("lop3.b32 %0, %1, %0, 1023, 0xD8;" : "+r"(fa[j]) : "r"(t));
                }
            };
            fa[0] = fa[2] = a0;
            fa[1] = fa[3] = a1;
            const uint32_t tta = sb + SM_TT + su * 512;
            uint4 tt = lds128(tta);
            flush(tt.x, false);
            const uint32_t ifirst = dlo(sb + SM_IND + su * 4096), ilast = ifirst + 1024;
            uint32_t iprev = ifirst, icur = ifirst;
            const uint32_t x0 = dlo(sb + SM_XE + su * XE_S), bar0 = sb + SM_BAR + 2 * su * 8;
            {
                const uint32_t xa = sb + SM_XE + su * XE_S + ((warp & 7) * 16 + (lane >> 3) * 2) * 128 + (((lane & 7) ^ ((lane >> 3) * 2)) << 4);
#pragma unroll
                for (int j = 0; j < 4; j++)
                    sts128((xa + (j & 1) * 1024 + (j >> 1) * 128) ^ ((j >> 1) << 4), bf2h(xv[j].x), bf2h(xv[j].y), bf2h(xv[j].z), bf2h(xv[j].w));
                __syncwarp();
                if (elect()) asm volatile("mbarrier.arrive.shared::cta.b64 _, [%0], 16;" ::"r"(bar0) : "memory");
                CSTAMP(27, tid == 64);
            }
            for (int k = 0; k < Ts; k++) {
                const uint32_t dx = x0 + (k & 1) * (XE_P >> 4), bar = bar0 + (k & 1) * 8;
                mbar_wait(bar, (k >> 1) & 1);
                if (k < KF) fence_async();
                wg_fence();
#pragma unroll
                for (int kk = 0; kk < 4; kk++) r16t(agg, pk + 4 * kk, dsc(iprev + kk * 64, DH32A));
                wg_commit();
                h128z(acc, w1f[0], dsc(dx, DH128));
                h128(acc, w1f[1], dsc(dx + 2, DH128));
                h128(acc, w1f[2], dsc(dx + 4, DH128));
                h128(acc, w1f[3], dsc(dx + 6, DH128));
                h128(acc, w1f[4], dsc(dx + 1024, DH32B));
                h128s(acc, dsc(tt.y + hu * 1536, tt.z), dsc(icur, DH32B));
                wg_commit();
                wg_wait<1>();
                fence_regs<8>(agg);
                fence_regs<16>(pk);
                flush(tt.x, true);
                tt = lds128(tta + (k + 1) * 16);
                wg_wait<0>();
                fence_regs<32>(acc);
                if (elect()) mbar_arrive(bar + 32);
#pragma unroll
                for (int i = 0; i < 16; i++) {
                    const int i0 = (i >> 1) * 4 + (i & 1);
                    pk[i] = hadd2(silu_h2(acc[i0]), silu_h2(acc[i0 + 2]));
                }
                fence_regs<16>(pk);
                iprev = icur;
                icur = icur == ilast ? ifirst : icur + 512;
            }
            wg_fence();
#pragma unroll
            for (int kk = 0; kk < 4; kk++) r16t(agg, pk + 4 * kk, dsc(iprev + kk * 64, DH32A));
            wg_commit();
            wg_wait<0>();
            fence_regs<8>(agg);
            flush(tt.x, true);
            if (Tu > 1) {
                const int sl = (tt.x >> 6) & 15;
                const bool mine = q == ((sl & 7) >> 1);
                const uint32_t xa = sb + SM_XB + hu * 256 + (warp4 * 8 + (lane >> 2)) * 8;
                const float v0 = (sl & 8) ? ((sl & 1) ? agg[5] : agg[4]) : ((sl & 1) ? agg[1] : agg[0]);
                const float v1 = (sl & 8) ? ((sl & 1) ? agg[7] : agg[6]) : ((sl & 1) ? agg[3] : agg[2]);
                if (su) {
                    if (mine) sts64(xa, __float_as_uint(v0), __float_as_uint(v1));
                    if (hu) bar_arrive<8, 256>(); else bar_arrive<7, 256>();
                } else {
                    if (hu) bar_sync<8, 256>(); else bar_sync<7, 256>();
                    const uint32_t ra = (sl & 8) ? ((sl & 1) ? fa[3] : fa[2]) + 12288 : ((sl & 1) ? fa[1] : fa[0]);
                    if (mine) sts32(ra, pack2(v0 + __uint_as_float(lds32(xa)), v1 + __uint_as_float(lds32(xa + 4))));
                }
            }
        }
    }
    CSTAMP(10, tid == 0);
    fence_async();
    bar_sync<1, NT>();
    if (wg < 3) tail_gemm<1>(sb, wg, warp4, lane, cta, a.out);
    else tail_scan(sb, tid - 384);
    CSTAMP(15, tid == 0);
    if (!tail_failed(sb) || T == 0) return false;
    asm volatile("setmaxnreg.dec.sync.aligned.u32 96;");
    return true;
}

template <int MODE>
__global__ void __launch_bounds__(NT, 1) mpnn_kernel(const __grid_constant__ Args a) {
    extern __shared__ __align__(1024) uint8_t smem[];
    const uint32_t sb = (uint32_t)__cvta_generic_to_shared(smem);
    TSTAMP(0, threadIdx.x == 0);
    CSTAMP(1, threadIdx.x == 0);
    const bool slow = threadIdx.x >= 512 ? producer<MODE>(sb, a) : consumer<MODE>(sb, a);
    if ((MODE & 2) && slow) slow_path(sb, blockIdx.x, a);
    CSTAMP(11, threadIdx.x == 0);
    TSTAMP(12, threadIdx.x == 0);
}

}

extern "C" void kernel_launch(void* const* d_in, const int* in_sizes, int n_in, void* d_out, int out_size) {
    (void)in_sizes; (void)n_in; (void)out_size;
    static int fused = -1;
    static void *p_ra, *p_rx, *p_xh, *p_ctl;
    if (fused < 0) {
        cudaGetSymbolAddress(&p_ra, g_ra);
        cudaGetSymbolAddress(&p_rx, g_rx);
        cudaGetSymbolAddress(&p_xh, g_xh);
        cudaGetSymbolAddress(&p_ctl, g_ctl);
        int dev = 0, sms = 0, nb = 0;
        cudaGetDevice(&dev);
        cudaDeviceGetAttribute(&sms, cudaDevAttrMultiProcessorCount, dev);
        cudaFuncSetAttribute(mpnn_kernel<1>, cudaFuncAttributeMaxDynamicSharedMemorySize, SM_TOTAL);
        cudaFuncSetAttribute(mpnn_kernel<2>, cudaFuncAttributeMaxDynamicSharedMemorySize, SM_TOTAL);
        cudaFuncSetAttribute(mpnn_kernel<3>, cudaFuncAttributeMaxDynamicSharedMemorySize, SM_TOTAL);
        cudaOccupancyMaxActiveBlocksPerMultiprocessor(&nb, mpnn_kernel<3>, NT, SM_TOTAL);
        fused = (sms * nb >= G) ? 1 : 0;
    }
    Args a;
    a.x   = (const __nv_bfloat16*)d_in[0];
    a.ea  = (const __nv_bfloat16*)d_in[1];
    a.src = (const int*)d_in[2];
    a.dst = (const int*)d_in[3];
    a.w1  = (const __nv_bfloat16*)d_in[4];
    a.b1  = (const __nv_bfloat16*)d_in[5];
    a.w2  = (const __nv_bfloat16*)d_in[6];
    a.b2  = (const __nv_bfloat16*)d_in[7];
    a.out = (__nv_bfloat16*)d_out;
    a.ra  = (uint4*)p_ra;
    a.rx  = (uint2*)p_rx;
    a.xh  = (uint4*)p_xh;
    a.ctl = (uint32_t*)p_ctl;
    cudaStream_t s = cudaStreamPerThread;
    if (fused) {
        mpnn_kernel<3><<<G, NT, SM_TOTAL, s>>>(a);
    } else {
        mpnn_kernel<1><<<G, NT, SM_TOTAL, s>>>(a);
        mpnn_kernel<2><<<G, NT, SM_TOTAL, s>>>(a);
    }
}
```

```cpp
#include <cuda_runtime.h>
#include <cuda_bf16.h>
#include <stdint.h>

#define RELX 0
#define PDT 200
#define PROWS 16
#define KF 2
#define PFA 4
#define PFB 4
#define XAT 0
#define TWG __shfl_sync(0xFFFFFFFFu, wg, 0)
#define PFL 3
#define SRCP 2
#define RPV 288
#define BXF 1
#define W1P 0
#define XRP 0
#define PTL 512
#define LATEW 1
#define STG 170
#define NPL 4
#define PDL 0
#define EL 0
#define GD 0
#define SRS 0
#define LENP 0
#define WA 0
#define SUNR 3
#define PRAGMA_(x) _Pragma(#x)
#define PRAGMA_UNROLL(n) PRAGMA_(unroll n)
#define NSH 5
namespace {

constexpr int NN   = 25000;
constexpr int NE   = 800000;
constexpr int G    = 132;
constexpr int NPB  = 190;
constexpr int CH   = 6064;
constexpr int CAPT = 52;
constexpr int CAP  = CAPT * 128;
constexpr int NT   = 640;
constexpr int CAPB = 48;
constexpr int OVC  = 64;
constexpr int BINP = CAPB * 4 + 4;
constexpr int RP   = RPV;
constexpr int RS   = RP / 4, RU = RP / 16, RX = 32;
constexpr uint32_t CINC = (1u << 18) + 4u;
constexpr uint32_t RUNL = (uint32_t)RS << 18, BINL = (uint32_t)(CAPB + 1) << 18;
constexpr uint32_t TAGM = 511u << 13, PADW = 0x800000u;

constexpr int SM_CNT  = 0;
constexpr int SM_DEG  = 576;
constexpr int SM_FLAG = SM_DEG + 896;
constexpr int SM_TT   = SM_FLAG + 48;
constexpr int SM_B1   = SM_TT + 1024;
constexpr int SM_B2   = SM_B1 + 256;
constexpr int SM_BAR  = SM_B2 + 128;
constexpr int SM_PIN  = SM_BAR + 96;
constexpr int SM_WT   = SM_PIN + 16;
constexpr int SM_XC   = SM_WT + 16;
constexpr int SM_XE   = 5120;
constexpr int XE_S    = 20480, XE_P = 65536;
constexpr int SM_IND  = SM_XE + 2 * XE_S;
constexpr int SM_POS  = SM_XE + XE_P + 2 * XE_S;
constexpr int SM_RAW  = 126976;
constexpr int SM_QA   = SM_RAW + 16384;
constexpr int SM_BIN  = SM_QA + 49152;
constexpr int SM_OVL  = SM_BIN + NPB * BINP;
constexpr int SM_SR   = SM_OVL + OVC * 8 + 8;
constexpr int SM_TOTAL = SM_SR + 2048;
constexpr uint32_t OVLO = SM_OVL - SM_BIN, PADO = OVLO + OVC * 8;
constexpr int F_TOT = SM_FLAG, F_DMAX = SM_FLAG + 4, F_BAD = SM_FLAG + 8, F_WMAX = SM_FLAG + 12, F_EARLY = SM_FLAG + 16,
              F_W2 = SM_FLAG + 24, F_XC = SM_FLAG + 28, F_MID = SM_FLAG + 32, F_UN = SM_FLAG + 36, F_ROWS = SM_FLAG + 40;
constexpr int SM_STA  = SM_XE;
constexpr int SM_XO   = SM_IND;
constexpr int SM_XR   = SM_XE + XE_P;
constexpr int SM_W1B  = SM_XR + 24576;
constexpr int SM_W1A  = SM_POS;
constexpr int SM_UT   = SM_W1A + 20480;
constexpr int B_X = SM_BAR + 64, B_W = SM_BAR + 72, B_V = SM_BAR + 80, B_T = SM_BAR + 88;
constexpr int SM_W2   = SM_BIN;
constexpr int SM_OUT  = SM_W2 + 17408;
constexpr int SM_DG   = SM_RAW;
constexpr int SM_ZR   = SM_POS + CAP * 2;
constexpr int SM_SAGG = SM_XE;
constexpr int SM_SQ   = SM_SAGG + NPB * 512;
constexpr int SM_SW   = SM_SQ + NPB * 512;
static_assert(RX == 32 && XAT >= 0 && B_T + 8 <= SM_PIN && RU >= 8 && 32 + G * (RU - 8) <= 2816 && SM_PIN % 16 == 0 && SM_XC + G * 4 <= SM_STA && SM_UT + 2816 * 4 <= SM_QA && SM_IND + 24576 == SM_XE + XE_P && SM_ZR + 640 <= SM_RAW && SM_ZR % 128 == 0 && NPB + 2 <= 192 && CAPB + OVC < 128 && CAPT / 2 + 2 <= 32 && SM_STA + G * RP <= SM_IND, "map");
static_assert(SM_OUT + 16384 <= SM_OVL && F_EARLY % 8 == 0 && SM_W1B + 16384 <= SM_POS && SM_W1A + 20480 <= SM_QA, "map");
static_assert(SM_SQ <= SM_QA && SM_SW + 20480 <= SM_TOTAL && SM_TOTAL <= 232448 && PADO < 65536, "map");
static_assert(G * (RS + RX) + 2 < 16384 && G * RU <= 5 * 512 && G == 132 && RU <= 24 && G * G * RU < (1 << 24) && G * CH >= NE && NE - (G - 1) * CH > 4096 && CH <= 6144 && CH % 4 == 0, "fields");
static_assert(SM_W2 % 1024 == 0 && SM_QA % 1024 == 0 && SM_XO % 1024 == 0 && SM_W1A % 1024 == 0 && SM_W1B % 1024 == 0 &&
              SM_B1 % 16 == 0 && SM_TT % 16 == 0 && SM_BAR % 8 == 0 && SM_STA % 16 == 0 && SM_OVL % 8 == 0 && SM_XR % 16 == 0 && SM_SR % 16 == 0 && SM_DEG % 16 == 0, "align");

constexpr int C_LEN = (G + 1) * 32;
__device__ uint4 g_ra[G * G * RU];
__device__ uint2 g_rx[G * G * RX];
__device__ uint4 g_xh[(NN + 1) * 8];
__device__ uint4 g_w2[129 * 8 + 1];
__device__ uint32_t g_ctl[C_LEN + G * 160];
#define CSTAMPV(i, cond)
#undef LOOPT
#define TSTAMP(i, cond)
#define CSTAMP(i, cond)

#define LSTAMP(w, k)
__device__ __forceinline__ uint64_t mkdesc(uint32_t addr, uint32_t lbo, uint32_t sbo, uint32_t swz) {
    return (uint64_t)((addr & 0x3FFFF) >> 4) | ((uint64_t)(lbo >> 4) << 16) | ((uint64_t)(sbo >> 4) << 32) |
           ((uint64_t)swz << 62);
}
__device__ __forceinline__ void wg_fence()  { asm volatile("wgmma.fence.sync.aligned;" ::: "memory"); }
__device__ __forceinline__ void wg_commit() { asm volatile("wgmma.commit_group.sync.aligned;" ::: "memory"); }
template <int N> __device__ __forceinline__ void wg_wait() { asm volatile("wgmma.wait_group.sync.aligned %0;" ::"n"(N) : "memory"); }
__device__ __forceinline__ void fence_async() { asm volatile("fence.proxy.async.shared::cta;" ::: "memory"); }

#define R8(d, o) "+f"(d[o + 0]), "+f"(d[o + 1]), "+f"(d[o + 2]), "+f"(d[o + 3]), "+f"(d[o + 4]), "+f"(d[o + 5]), "+f"(d[o + 6]), "+f"(d[o + 7])
#define W8(d, o) "=f"(d[o + 0]), "=f"(d[o + 1]), "=f"(d[o + 2]), "=f"(d[o + 3]), "=f"(d[o + 4]), "=f"(d[o + 5]), "=f"(d[o + 6]), "=f"(d[o + 7])
#define U8(d, o) "+r"(d[o + 0]), "+r"(d[o + 1]), "+r"(d[o + 2]), "+r"(d[o + 3]), "+r"(d[o + 4]), "+r"(d[o + 5]), "+r"(d[o + 6]), "+r"(d[o + 7])
#define V8(d, o) "=r"(d[o + 0]), "=r"(d[o + 1]), "=r"(d[o + 2]), "=r"(d[o + 3]), "=r"(d[o + 4]), "=r"(d[o + 5]), "=r"(d[o + 6]), "=r"(d[o + 7])
#define L24 "{%0,%1,%2,%3,%4,%5,%6,%7,%8,%9,%10,%11,%12,%13,%14,%15,%16,%17,%18,%19,%20,%21,%22,%23}"
#define L32 "{%0,%1,%2,%3,%4,%5,%6,%7,%8,%9,%10,%11,%12,%13,%14,%15,%16,%17,%18,%19,%20,%21,%22,%23,%24,%25,%26,%27,%28,%29,%30,%31}"
#define L48 "{%0,%1,%2,%3,%4,%5,%6,%7,%8,%9,%10,%11,%12,%13,%14,%15,%16,%17,%18,%19,%20,%21,%22,%23,%24,%25,%26,%27,%28,%29,%30,%31,%32,%33,%34,%35,%36,%37,%38,%39,%40,%41,%42,%43,%44,%45,%46,%47}"

__device__ __forceinline__ void h128z(uint32_t* d, const uint32_t* a, uint64_t db) {
    asm volatile("{.reg .pred p; setp.ne.b32 p, 0, 0;\n"
                 "wgmma.mma_async.sync.aligned.m64n128k16.f16.f16.f16 " L32 ", {%32,%33,%34,%35}, %36, p, 1, 1, 0;}"
                 : V8(d, 0), V8(d, 8), V8(d, 16), V8(d, 24) : "r"(a[0]), "r"(a[1]), "r"(a[2]), "r"(a[3]), "l"(db));
}
__device__ __forceinline__ void h128(uint32_t* d, const uint32_t* a, uint64_t db) {
    asm volatile("{.reg .pred p; setp.eq.b32 p, 0, 0;\n"
                 "wgmma.mma_async.sync.aligned.m64n128k16.f16.f16.f16 " L32 ", {%32,%33,%34,%35}, %36, p, 1, 1, 0;}"
                 : U8(d, 0), U8(d, 8), U8(d, 16), U8(d, 24) : "r"(a[0]), "r"(a[1]), "r"(a[2]), "r"(a[3]), "l"(db));
}
__device__ __forceinline__ void h16t(uint32_t* d, const uint32_t* a, uint64_t db) {
    asm volatile("{.reg .pred p; setp.eq.b32 p, 0, 0;\n"
                 "wgmma.mma_async.sync.aligned.m64n16k16.f16.f16.f16 {%0,%1,%2,%3}, {%4,%5,%6,%7}, %8, p, 1, 1, 1;}"
                 : "+r"(d[0]), "+r"(d[1]), "+r"(d[2]), "+r"(d[3]) : "r"(a[0]), "r"(a[1]), "r"(a[2]), "r"(a[3]), "l"(db));
}
__device__ __forceinline__ void rs64z(float* d, const uint32_t* a, uint64_t db) {
    asm volatile("{.reg .pred p; setp.ne.b32 p, 0, 0;\n"
                 "wgmma.mma_async.sync.aligned.m64n64k16.f32.f16.f16 " L32 ", {%32,%33,%34,%35}, %36, p, 1, 1, 0;}"
                 : W8(d, 0), W8(d, 8), W8(d, 16), W8(d, 24) : "r"(a[0]), "r"(a[1]), "r"(a[2]), "r"(a[3]), "l"(db));
}
__device__ __forceinline__ void rs64(float* d, const uint32_t* a, uint64_t db) {
    asm volatile("{.reg .pred p; setp.eq.b32 p, 0, 0;\n"
                 "wgmma.mma_async.sync.aligned.m64n64k16.f32.f16.f16 " L32 ", {%32,%33,%34,%35}, %36, p, 1, 1, 0;}"
                 : R8(d, 0), R8(d, 8), R8(d, 16), R8(d, 24) : "r"(a[0]), "r"(a[1]), "r"(a[2]), "r"(a[3]), "l"(db));
}
__device__ __forceinline__ void rs8(float* d, const uint32_t* a, uint64_t db) {
    asm volatile("{.reg .pred p; setp.eq.b32 p, 0, 0;\n"
                 "wgmma.mma_async.sync.aligned.m64n8k16.f32.f16.f16 {%0,%1,%2,%3}, {%4,%5,%6,%7}, %8, p, 1, 1, 0;}"
                 : "+f"(d[0]), "+f"(d[1]), "+f"(d[2]), "+f"(d[3]) : "r"(a[0]), "r"(a[1]), "r"(a[2]), "r"(a[3]), "l"(db));
}
__device__ __forceinline__ void q_gemm(float* d, uint64_t da, uint64_t db) {
    asm volatile("{.reg .pred p, q; .reg .b64 a, b; setp.ne.b32 p, 0, 0; setp.eq.b32 q, 0, 0;\n"
                 "wgmma.fence.sync.aligned;\n"
                 "wgmma.mma_async.sync.aligned.m64n96k16.f32.bf16.bf16 " L48 ", %48, %49, p, 1, 1, 1, 0;\n"
                 "add.s64 a, %48, 128; add.s64 b, %49, 2;\n"
                 "wgmma.mma_async.sync.aligned.m64n96k16.f32.bf16.bf16 " L48 ", a, b, q, 1, 1, 1, 0;\n"
                 "add.s64 a, %48, 256; add.s64 b, %49, 4;\n"
                 "wgmma.mma_async.sync.aligned.m64n96k16.f32.bf16.bf16 " L48 ", a, b, q, 1, 1, 1, 0;\n"
                 "add.s64 a, %48, 384; add.s64 b, %49, 6;\n"
                 "wgmma.mma_async.sync.aligned.m64n96k16.f32.bf16.bf16 " L48 ", a, b, q, 1, 1, 1, 0;\n"
                 "wgmma.commit_group.sync.aligned;}"
                 : W8(d, 0), W8(d, 8), W8(d, 16), W8(d, 24), W8(d, 32), W8(d, 40)
                 : "l"(da), "l"(db) : "memory");
}
__device__ __forceinline__ void ss64t(float* d, uint64_t da, uint64_t db, int acc) {
    asm volatile("{.reg .pred p; setp.ne.b32 p, %34, 0;\n"
                 "wgmma.mma_async.sync.aligned.m64n64k16.f32.bf16.bf16 " L32 ", %32, %33, p, 1, 1, 0, 1;}"
                 : R8(d, 0), R8(d, 8), R8(d, 16), R8(d, 24)
                 : "l"(da), "l"(db), "r"(acc));
}
template <int NREG> __device__ __forceinline__ void fence_regs(float* d) {
#pragma unroll
    for (int i = 0; i < NREG; i++) asm volatile("" : "+f"(d[i])::"memory");
}
template <int NREG> __device__ __forceinline__ void fence_regs(uint32_t* d) {
#pragma unroll
    for (int i = 0; i < NREG; i++) asm volatile("" : "+r"(d[i])::"memory");
}
__device__ __forceinline__ void ldsm4t(uint32_t* r, uint32_t addr) {
    asm volatile("ldmatrix.sync.aligned.m8n8.x4.trans.shared.b16 {%0,%1,%2,%3}, [%4];"
                 : "=r"(r[0]), "=r"(r[1]), "=r"(r[2]), "=r"(r[3]) : "r"(addr) : "memory");
}
__device__ __forceinline__ uint32_t movm(uint32_t a) {
    uint32_t d; asm volatile("movmatrix.sync.aligned.m8n8.trans.b16 %0, %1;" : "=r"(d) : "r"(a)); return d;
}
__device__ __forceinline__ void stsm4t(uint32_t addr, uint32_t a, uint32_t b, uint32_t c, uint32_t d) {
    asm volatile("stmatrix.sync.aligned.m8n8.x4.trans.shared.b16 [%0], {%1,%2,%3,%4};" ::"r"(addr), "r"(a), "r"(b), "r"(c), "r"(d) : "memory");
}
__device__ __forceinline__ void cp16(uint32_t s, const void* g) {
    asm volatile("cp.async.cg.shared.global [%0], [%1], 16;" ::"r"(s), "l"(g) : "memory");
}
__device__ __forceinline__ void cp4(uint32_t s, const void* g) {
    asm volatile("cp.async.ca.shared.global [%0], [%1], 4;" ::"r"(s), "l"(g) : "memory");
}
__device__ __forceinline__ void cp16z(uint32_t s, const void* g, uint32_t skip) {
    asm volatile("{.reg .pred p; setp.ne.u32 p, %2, 0; cp.async.cg.shared.global [%0], [%1], 16, p;}" ::"r"(s), "l"(g), "r"(skip) : "memory");
}
__device__ __forceinline__ void cp_commit() { asm volatile("cp.async.commit_group;" ::: "memory"); }
template <int N> __device__ __forceinline__ void cp_wait() { asm volatile("cp.async.wait_group %0;" ::"n"(N) : "memory"); }
__device__ __forceinline__ void cp_wait_all() { asm volatile("cp.async.wait_all;" ::: "memory"); }
__device__ __forceinline__ void mbar_init(uint32_t a, int cnt) { asm volatile("mbarrier.init.shared::cta.b64 [%0], %1;" ::"r"(a), "r"(cnt) : "memory"); }
__device__ __forceinline__ void mbar_arrive(uint32_t a) { asm volatile("mbarrier.arrive.shared::cta.b64 _, [%0];" ::"r"(a) : "memory"); }
__device__ __forceinline__ void mbar_cp_arrive(uint32_t a) { asm volatile("cp.async.mbarrier.arrive.noinc.shared::cta.b64 [%0];" ::"r"(a) : "memory"); }
__device__ __forceinline__ void mbar_wait(uint32_t a, uint32_t parity) {
    asm volatile("{.reg .pred p; .reg .u32 n; mov.u32 n, 0;\n"
                 "MW_%=: mbarrier.try_wait.parity.shared::cta.b64 p, [%0], %1;\n"
                 "@p bra MD_%=;\n"
                 "add.u32 n, n, 1; setp.gt.u32 p, n, 0x100000;\n"
                 "@p trap;\n"
                 "bra MW_%=;\n"
                 "MD_%=: }" ::"r"(a), "r"(parity) : "memory");
}
template <int ID, int CNT> __device__ __forceinline__ void bar_sync()   { asm volatile("bar.sync %0, %1;" ::"n"(ID), "n"(CNT) : "memory"); }
template <int ID, int CNT> __device__ __forceinline__ void bar_arrive() { asm volatile("bar.arrive %0, %1;" ::"n"(ID), "n"(CNT) : "memory"); }
template <int ID, int CNT> __device__ __forceinline__ bool bar_or(bool c) {
    uint32_t r;
    asm volatile("{.reg .pred p, q; setp.ne.u32 q, %1, 0; bar.red.or.pred p, %2, %3, q; selp.u32 %0, 1, 0, p;}" : "=r"(r) : "r"((uint32_t)c), "n"(ID), "n"(CNT) : "memory");
    return r != 0;
}
__device__ __forceinline__ float tanh_fast(float x) { float y; asm("tanh.approx.f32 %0, %1;" : "=f"(y) : "f"(x)); return y; }
__device__ __forceinline__ uint32_t pack2(float lo, float hi) {
    uint32_t r; asm("cvt.rn.bf16x2.f32 %0, %1, %2;" : "=r"(r) : "f"(hi), "f"(lo)); return r;
}
__device__ __forceinline__ uint32_t pack2h(float lo, float hi) {
    uint32_t r; asm("cvt.rn.f16x2.f32 %0, %1, %2;" : "=r"(r) : "f"(hi), "f"(lo)); return r;
}
__device__ __forceinline__ float bf_lo(uint32_t v) { return __uint_as_float(v << 16); }
__device__ __forceinline__ float bf_hi(uint32_t v) { return __uint_as_float(v & 0xFFFF0000u); }
__device__ __forceinline__ uint32_t bf2h(uint32_t v) { return pack2h(bf_lo(v), bf_hi(v)); }
__device__ __forceinline__ uint32_t amax2(uint32_t a, uint32_t b) {
    uint32_t r; asm("max.NaN.xorsign.abs.bf16x2 %0, %1, %2;" : "=r"(r) : "r"(a), "r"(b)); return r;
}
__device__ __forceinline__ uint32_t hmax2(uint32_t a, uint32_t b) {
    uint32_t r; asm("max.NaN.xorsign.abs.f16x2 %0, %1, %2;" : "=r"(r) : "r"(a), "r"(b)); return r;
}
__device__ __forceinline__ float h2f(uint32_t v) { float f; asm("{.reg .b16 l, h; mov.b32 {l, h}, %1; cvt.f32.f16 %0, l;}" : "=f"(f) : "r"(v)); return f; }
__device__ __forceinline__ uint32_t amax_fin(uint32_t m) { return max(m & 0x7FFFu, (m >> 16) & 0x7FFFu); }
__device__ __forceinline__ uint32_t silu_h2(uint32_t h) {
    uint32_t t, s;
    asm("tanh.approx.f16x2 %0, %1;" : "=r"(t) : "r"(h));
    asm("fma.rn.f16x2 %0, %1, %2, %1;" : "=r"(s) : "r"(h), "r"(t));
    return s;
}
__device__ __forceinline__ uint32_t hadd2(uint32_t a, uint32_t b) { uint32_t s; asm("add.rn.f16x2 %0, %1, %2;" : "=r"(s) : "r"(a), "r"(b)); return s; }
__device__ __forceinline__ uint32_t bmul2(uint32_t a, uint32_t b) { uint32_t s; asm("mul.rn.bf16x2 %0, %1, %2;" : "=r"(s) : "r"(a), "r"(b)); return s; }
__device__ __forceinline__ uint32_t lds32(uint32_t a) { uint32_t v; asm volatile("ld.shared.b32 %0, [%1];" : "=r"(v) : "r"(a) : "memory"); return v; }
__device__ __forceinline__ uint32_t lds16(uint32_t a) { uint32_t v; asm volatile("ld.shared.u16 %0, [%1];" : "=r"(v) : "r"(a) : "memory"); return v; }
__device__ __forceinline__ uint4 lds128(uint32_t a) {
    uint4 v; asm volatile("ld.shared.v4.b32 {%0,%1,%2,%3}, [%4];" : "=r"(v.x), "=r"(v.y), "=r"(v.z), "=r"(v.w) : "r"(a) : "memory"); return v;
}
__device__ __forceinline__ void sts16(uint32_t a, uint32_t v) { asm volatile("st.shared.u16 [%0], %1;" ::"r"(a), "r"(v) : "memory"); }
__device__ __forceinline__ void sts32(uint32_t a, uint32_t v) { asm volatile("st.shared.b32 [%0], %1;" ::"r"(a), "r"(v) : "memory"); }
__device__ __forceinline__ void sts64(uint32_t a, uint32_t x, uint32_t y) { asm volatile("st.shared.v2.b32 [%0], {%1,%2};" ::"r"(a), "r"(x), "r"(y) : "memory"); }
__device__ __forceinline__ void sts128(uint32_t a, uint32_t x, uint32_t y, uint32_t z, uint32_t w) {
    asm volatile("st.shared.v4.b32 [%0], {%1,%2,%3,%4};" ::"r"(a), "r"(x), "r"(y), "r"(z), "r"(w) : "memory");
}
template <uint32_t V> __device__ __forceinline__ uint32_t atoms_add(uint32_t a) {
    uint32_t v; asm volatile("atom.shared.add.u32 %0, [%1], %2;" : "=r"(v) : "r"(a), "n"(V) : "memory"); return v;
}
__device__ __forceinline__ uint2 lds64(uint32_t a) {
    uint2 v; asm volatile("ld.shared.v2.b32 {%0,%1}, [%2];" : "=r"(v.x), "=r"(v.y) : "r"(a) : "memory"); return v;
}
__device__ __forceinline__ void st_rel64(void* p, uint32_t x, uint32_t y) {
    asm volatile("st.relaxed.gpu.global.b64 [%0], %1;" ::"l"(p), "l"((uint64_t)x | ((uint64_t)y << 32)) : "memory");
}
__device__ __forceinline__ uint64_t ld_rel64(const void* p) {
    uint64_t v; asm volatile("ld.relaxed.gpu.global.b64 %0, [%1];" : "=l"(v) : "l"(p) : "memory"); return v;
}
__device__ __forceinline__ uint32_t ld_acq32(const void* p) {
    uint32_t v; asm volatile("ld.acquire.gpu.global.b32 %0, [%1];" : "=r"(v) : "l"(p) : "memory"); return v;
}
__device__ __forceinline__ void st_rlx32(void* p, uint32_t x) { asm volatile("st.relaxed.gpu.global.u32 [%0], %1;" ::"l"(p), "r"(x) : "memory"); }
__device__ __forceinline__ uint32_t ld_rlx32(const void* p) {
    uint32_t v; asm volatile("ld.relaxed.gpu.global.u32 %0, [%1];" : "=r"(v) : "l"(p) : "memory"); return v;
}
__device__ __forceinline__ uint32_t ld_g32(const void* p) {
    uint32_t v; asm volatile("ld.global.b32 %0, [%1];" : "=r"(v) : "l"(p) : "memory"); return v;
}
__device__ __forceinline__ uint4 ld_stream(const void* p) {
    uint4 v;
    asm volatile("ld.global.nc.L1::no_allocate.v4.b32 {%0,%1,%2,%3}, [%4];" : "=r"(v.x), "=r"(v.y), "=r"(v.z), "=r"(v.w) : "l"(p) : "memory");
    return v;
}
__device__ __forceinline__ uint32_t atoms_addr(uint32_t a, uint32_t inc) {
    uint32_t v; asm volatile("atom.shared.add.u32 %0, [%1], %2;" : "=r"(v) : "r"(a), "r"(inc) : "memory"); return v;
}
template <uint32_t LIM, uint32_t BIT> __device__ __forceinline__ void put(uint32_t v, uint32_t w, uint32_t& mask) {
    asm volatile("{.reg .pred q, o; .reg .u32 t; setp.lt.u32 q|o, %1, %3; and.b32 t, %1, 0x3FFFF;\n"
                 "@q st.shared.b32 [t], %2; @o or.b32 %0, %0, %4;}" : "+r"(mask) : "r"(v), "r"(w), "n"(LIM), "n"(BIT) : "memory");
}
template <uint32_t LIM> __device__ __forceinline__ void put(uint32_t v, uint32_t w) {
    asm volatile("{.reg .pred q; .reg .u32 t; setp.lt.u32 q, %0, %2; and.b32 t, %0, 0x3FFFF; @q st.shared.b32 [t], %1;}"
                 ::"r"(v), "r"(w), "n"(LIM) : "memory");
}
__device__ __forceinline__ uint4 ld_rec(const uint4* p) {
    uint4 v;
    asm volatile("ld.relaxed.gpu.global.v4.b32 {%0,%1,%2,%3}, [%4];" : "=r"(v.x), "=r"(v.y), "=r"(v.z), "=r"(v.w) : "l"(p) : "memory");
    return v;
}
__device__ __forceinline__ void ld_rec_if(uint4& v, bool c, const uint4* p) {
    asm volatile("{.reg .pred q; setp.ne.u32 q, %5, 0; @q ld.relaxed.gpu.global.v4.b32 {%0,%1,%2,%3}, [%4];}"
                 : "+r"(v.x), "+r"(v.y), "+r"(v.z), "+r"(v.w) : "l"(p), "r"((uint32_t)c) : "memory");
}
__device__ __forceinline__ void pin(uint32_t c, uint32_t a, uint32_t x, uint32_t y, uint32_t z, uint32_t w) {
    asm volatile("{.reg .pred p; setp.eq.u32 p, %0, 0; @p st.shared.v4.b32 [%1], {%2, %3, %4, %5};}" ::"r"(c), "r"(a), "r"(x), "r"(y), "r"(z), "r"(w) : "memory");
}
__device__ __forceinline__ void bulk_copy(void* g, uint32_t s, uint32_t bytes) {
    asm volatile("cp.async.bulk.global.shared::cta.bulk_group [%0], [%1], %2;" ::"l"(g), "r"(s), "r"(bytes) : "memory");
}
__device__ __forceinline__ void bulk_store(void* g, uint32_t s, uint32_t bytes) {
    asm volatile("cp.async.bulk.global.shared::cta.bulk_group [%0], [%1], %2;\n"
                 "cp.async.bulk.commit_group;" ::"l"(g), "r"(s), "r"(bytes) : "memory");
}
__device__ __forceinline__ void bulk_wait()      { asm volatile("cp.async.bulk.wait_group 0;" ::: "memory"); }
__device__ __forceinline__ void bulk_wait_read() { asm volatile("cp.async.bulk.wait_group.read 0;" ::: "memory"); }
__device__ __forceinline__ void l2_prefetch(const void* p, uint32_t bytes) {
    asm volatile("cp.async.bulk.prefetch.L2.global [%0], %1;" ::"l"(p), "r"(bytes) : "memory");
}
__device__ __forceinline__ const char* madw(uint32_t a, uint32_t b, const char* p) {
    const char* r; asm("mad.wide.u32 %0, %1, %2, %3;" : "=l"(r) : "r"(a), "r"(b), "l"(p)); return r;
}
__device__ __forceinline__ uint64_t dsc(uint32_t lo, uint32_t hi) { return (uint64_t)lo | ((uint64_t)hi << 32); }
__device__ __forceinline__ uint32_t dlo(uint32_t addr) { return ((addr & 0x3FFFF) >> 4) | 0x10000u; }
constexpr uint32_t DH128 = (1024 >> 4) | (1u << 30), DH32A = (512 >> 4) | (3u << 30), DH32B = (256 >> 4) | (3u << 30);
__device__ __forceinline__ bool elect() {
    uint32_t r;
    asm volatile("{.reg .pred p; elect.sync _|p, 0xFFFFFFFF; selp.u32 %0, 1, 0, p;}" : "=r"(r));
    return r != 0;
}
__device__ __forceinline__ int fresh_tid() { int t; asm volatile("mov.u32 %0, %%tid.x;" : "=r"(t)); return t; }
__device__ __forceinline__ int col2pos(int c) { return (c & ~15) | ((c & 7) << 1) | ((c >> 3) & 1); }

struct Args {
    uint32_t* ctl;
    const int* dst;
    uint4* ra;
    const __nv_bfloat16 *x, *w1, *b1;
    const int* src;
    const __nv_bfloat16 *ea, *w2, *b2;
    __nv_bfloat16* out;
    uint4* xh;
    uint2* rx;
    uint4* w2h;
};

__device__ __forceinline__ void bin_overflow(uint32_t sb, uint32_t rec, uint32_t v) {
    const uint32_t ix = atoms_add<1>(sb + F_XC);
    if (ix < OVC) sts64(sb + SM_OVL + ix * 8, rec, v);
    else sts32(sb + F_BAD, 1u);
}
__device__ __forceinline__ void drop(uint32_t sb, const uint4& rv, uint32_t c0, uint32_t inc) {
    uint4 v;
    v.x = atoms_addr(sb + SM_DEG + (rv.x >> 22), inc);
    v.y = atoms_addr(sb + SM_DEG + (rv.y >> 22), inc);
    v.z = atoms_addr(sb + SM_DEG + (rv.z >> 22), inc);
    v.w = atoms_addr(sb + SM_DEG + (rv.w >> 22), inc);
    put<BINL>(v.x, rv.x + c0);
    put<BINL>(v.y, rv.y + c0);
    put<BINL>(v.z, rv.z + c0);
    put<BINL>(v.w, rv.w + c0);
    if (__builtin_expect(max(max((int)v.x, (int)v.y), max((int)v.z, (int)v.w)) >= (int)BINL, 0)) {
        if ((int)v.x >= (int)BINL) bin_overflow(sb, rv.x + c0, v.x);
        if ((int)v.y >= (int)BINL) bin_overflow(sb, rv.y + c0, v.y);
        if ((int)v.z >= (int)BINL) bin_overflow(sb, rv.z + c0, v.z);
        if ((int)v.w >= (int)BINL) bin_overflow(sb, rv.w + c0, v.w);
    }
}
__device__ __forceinline__ void await(uint4& rv, uint32_t tg, const uint4* p) {
    int it = 0;
    while (__builtin_expect(__any_sync(0xFFFFFFFFu, ((rv.x ^ tg) | (rv.y ^ tg) | (rv.z ^ tg) | (rv.w ^ tg)) & TAGM), 0)) {
        if (++it > (1 << 22)) __trap();
        ld_rec_if(rv, ((rv.x ^ tg) | (rv.y ^ tg) | (rv.z ^ tg) | (rv.w ^ tg)) & TAGM, p);
    }
}
__device__ __forceinline__ void send_extra(uint32_t sb, uint32_t mask, uint32_t ep, const Args& a) {
#pragma unroll 1
    while (mask) {
        const uint32_t i = __ffs(mask) - 1, off = threadIdx.x * 4 + (3 - (i >> 2)) * 2048 + (i & 3);
        mask &= mask - 1;
        const uint32_t d = a.dst[blockIdx.x * CH + off], b = __umulhi(d, 22605092u);
        const uint32_t ix = atoms_add<1>(sb + SM_XC + b * 4);
        if (ix < RX) st_rel64(a.rx + (b * G + blockIdx.x) * RX + ix, ((d - b * NPB) << 24) + off, ep);
    }
}
template <int MODE> __device__ __forceinline__ void recv_extra(uint32_t sb, uint32_t len, uint32_t from, uint32_t ep, const Args& a) {
    const uint32_t lane = threadIdx.x & 31;
    uint32_t m = __ballot_sync(0xFFFFFFFFu, len > RS);
#pragma unroll 1
    while (__builtin_expect(m != 0, 0)) {
        const int l = __ffs(m) - 1;
        m &= m - 1;
        const uint32_t n = __shfl_sync(0xFFFFFFFFu, len, l) - RS, run = __shfl_sync(0xFFFFFFFFu, from, l);
        if (n > RX) sts32(sb + F_BAD, 1u);
        else if (lane < n) {
            const uint2* p = a.rx + (blockIdx.x * G + run) * RX + lane;
            uint64_t w = ld_rel64(p);
            int it = 0;
            while (MODE == 3 && (uint32_t)(w >> 32) != ep) {
                if (++it > (1 << 22)) __trap();
                w = ld_rel64(p);
            }
            const uint32_t rec = (uint32_t)w + run * CH, v = atoms_add<CINC>(sb + SM_DEG + (rec >> 24) * 4);
            if (v < BINL) sts32(v & 0x3FFFFu, rec);
            else bin_overflow(sb, rec, v);
        }
        __syncwarp();
    }
}
__device__ __forceinline__ void load_w2(uint32_t sb, int u, int nthr, const Args& a) {
    for (int i = u; i < 128 * 32; i += nthr) {
        const int k = i >> 5, w = i & 31;
        cp4(sb + SM_W2 + k * 128 + (((w & 7) ^ (k & 7)) << 4) + (w >> 3) * 4, a.w2 + k * 64 + w * 2);
    }
    if (u < 8) cp16(sb + SM_B2 + u * 16, a.b2 + u * 8);
    cp_wait_all();
}
__device__ __forceinline__ void convert_w2(uint32_t sb, int u, uint32_t ep, const Args& a) {
    const uint4* wp = reinterpret_cast<const uint4*>(a.w2) + u * 2;
    const uint4* bp = reinterpret_cast<const uint4*>(a.b2) + (u & 3) * 2;
    auto mx = [](const uint4& v, const uint4& w) { return amax2(amax2(amax2(v.x, v.y), amax2(v.z, v.w)), amax2(amax2(w.x, w.y), amax2(w.z, w.w))); };
    uint32_t m = 0;
#pragma unroll 4
    for (int j = 0; j < 8; j++) m = amax2(m, mx(__ldg(wp + j * 128), __ldg(wp + j * 128 + 1)));
    const uint32_t mb = amax_fin(mx(__ldg(bp), __ldg(bp + 1)));
    m = amax_fin(m);
    bool bad = max(m, mb) >= 0x7F80u;
    m = __reduce_max_sync(0xFFFFFFFFu, max(m, max(mb, 0x400u) - 0x400u));
    if ((u & 31) == 0) asm volatile("red.shared.max.u32 [%0], %1;" ::"r"(sb + F_W2), "r"(m) : "memory");
    bar_sync<8, 64>();
    const uint32_t ex = max(lds32(sb + F_W2) >> 7, 15u);
#pragma unroll 1
    for (int j = 0; j < 9; j++) {
        const float sc = __uint_as_float((268u - ex) << 23) * (j < 8 ? 1.f : 1.f / 256.f);
        auto cv = [&](uint32_t w) {
            const float lo = bf_lo(w) * sc, hi = bf_hi(w) * sc;
            const uint32_t r = pack2h(lo, hi);
            bad = bad || h2f(r) != lo || h2f(r >> 16) != hi;
            return r;
        };
        const uint4* p = j < 8 ? wp + j * 128 : bp;
        const uint4 v = __ldg(p), w = __ldg(p + 1);
        const uint32_t row = j < 8 ? j * 16 + (u >> 2) : 128, o = row * 8 + (((u & 3) * 2) ^ (row & 7));
        a.w2h[o] = make_uint4(cv(v.x), cv(v.y), cv(v.z), cv(v.w));
        a.w2h[o ^ 1] = make_uint4(cv(w.x), cv(w.y), cv(w.z), cv(w.w));
    }
    __threadfence();
    bad = bar_or<8, 64>(bad);
    if (u == 0) {
        st_rel64(a.w2h + 129 * 8, (ex - 14u) * 0x800080u, bad);
        asm volatile("st.release.gpu.global.b32 [%0], %1;" ::"l"(&a.w2h[129 * 8].z), "r"(ep) : "memory");
    }
    __syncwarp();
}
template <int MODE> __device__ __forceinline__ void prepare_tail(uint32_t sb, int u, uint32_t ep, const Args& a) {
    int it = 0;
    while (MODE == 3 && ld_acq32(&a.w2h[129 * 8].z) != ep)
        if (++it > (1 << 22)) __trap();
#pragma unroll
    for (int j = 0; j < 9; j++)
        if (j < 8 || u < 9) cp16(sb + SM_W2 + u * 16 + j * 2048, a.w2h + u + j * 128);
    mbar_cp_arrive(sb + B_W);
#pragma unroll
    for (int j = 0; j < 3; j++) {
        const uint32_t i = u + 128 * j, dg = (lds32(sb + SM_DEG + (i >> 1) * 4) >> 18) - 1;
        sts128(sb + SM_DG + i * 16, pack2h((float)dg * 256.f, 0.f), 0u, 0u, 0u);
        if (dg == 0 && (i < 2 * NPB || lds32(sb + F_MID) == NPB))
#pragma unroll 1
            for (int c = 0; c < 8; c++) sts128(sb + SM_QA + (i & 1) * 24576 + (i >> 1) * 128 + c * 16, 0u, 0u, 0u, 0u);
    }
    __syncwarp();
    fence_async();
    mbar_arrive(sb + B_W);
}
__device__ __forceinline__ bool sums_small(uint32_t sb, int u, int T0) {
    const float thr = (float)lds32(sb + F_DMAX) * (1.f / 32768.f) * fmaf(88.f, bf_lo(lds32(sb + F_WMAX)), 32.f);
    const uint32_t ra = sb + SM_QA + u * 16;
    auto mx = [&](int j) { const uint4 v = lds128(ra + j * 2048); return hmax2(hmax2(v.x, v.y), hmax2(v.z, v.w)); };
    const bool fin = lds32(sb + SM_TT + max(T0 - 4, 0) * 16) >= 2048u && lds32(sb + SM_DEG + (u >> 3) * 4) >= (2u << 18);
    if (bar_or<10, 128>(fin && h2f(amax_fin(hmax2(mx(0), mx(12)))) >= thr)) {
        bar_arrive<1, NT>();
        return false;
    }
    const uint32_t mid = lds32(sb + F_MID);
    bar_sync<1, NT>();
    if ((mid & 15) == (u >> 3)) { sts128(ra + (mid >> 4) * 2048, 0u, 0u, 0u, 0u); sts128(ra + (mid >> 4) * 2048 + 24576, 0u, 0u, 0u, 0u); }
    __syncwarp();
    uint32_t m = 0;
#pragma unroll 4
    for (int j = 0; j < 24; j++) m = hmax2(m, mx(j));
    return !bar_or<10, 128>(h2f(amax_fin(m)) >= thr);
}

template <int K0, int K1> __device__ __forceinline__ void load_w2t(uint32_t sb, int warp4, int lane, uint32_t (*af)[4]) {
    const int kr = (lane & 7) + 8 * (lane >> 4), ch = 2 * warp4 + ((lane >> 3) & 1);
    if (K0 == 0) mbar_wait(sb + B_W, 0);
#pragma unroll
    for (int ks = K0; ks < K1; ks++) ldsm4t(af[ks], sb + SM_W2 + (16 * ks + kr) * 128 + ((ch ^ (kr & 7)) << 4));
}
__device__ __forceinline__ bool tail(uint32_t sb, int wg, int T, int warp4, int lane, uint32_t (*af)[4], __nv_bfloat16* __restrict__ out) {
    const int late = ((wg >> 1) ^ T) & 1, blk = 2 * (wg & 1) + late, row0 = blk == 3 ? 184 : blk * 64;
    const int r = warp4 * 4 + (lane >> 3), n0 = row0 + r, nrow = min(NPB, NN - (int)blockIdx.x * NPB);
    const uint32_t db = dlo(sb + SM_QA + row0 * 128), dd = dlo(sb + SM_DG + row0 * 32);
    load_w2t<NSH, 8>(sb, warp4, lane, af);
    ldsm4t(af[8], sb + (lane & 23 ? SM_ZR : SM_W2 + 16384 + warp4 * 32) + (lane & 8) * 2);
    const int mid = lds32(sb + F_MID);
    const uint32_t sc = lds32(sb + SM_W2 + 129 * 128);
    const uint2 fe = lds64(sb + F_EARLY);
    uint32_t m = 0;
    out += (size_t)blockIdx.x * NPB * 64;
    fence_async();
    asm volatile("{.reg .pred p; setp.ne.u32 p, %0, 0; @p bar.arrive 1, %1; @!p bar.sync 1, %1;}" ::"r"(fe.x & fe.y & ~late), "n"(NT) : "memory");
    if (blk == 3) {
        float d[4] = {0.f, 0.f, 0.f, 0.f};
        wg_fence();
        rs8(d, af[8], dsc(dd, DH32B));
#pragma unroll
        for (int ks = 0; ks < 8; ks++) rs8(d, af[ks], dsc(db + (ks >> 2) * (24576 >> 4) + (ks & 3) * 2, DH128));
        wg_commit();
        wg_wait<0>();
        fence_regs<4>(d);
#pragma unroll
        for (int ks = 0; ks < 9; ks++) fence_regs<4>(af[ks]);
        m = pack2(d[0] + d[1], d[2] + d[3]);
        if ((lane & 3) == 3 && mid < NPB) {
            unsigned short* op = reinterpret_cast<unsigned short*>(out) + mid * 64 + warp4 * 16 + (lane >> 2);
            const uint32_t v = bmul2(m, sc);
            op[0] = v, op[8] = v >> 16;
        }
    } else {
        const uint32_t so = sb + (late ? SM_XE : SM_OUT + blk * 4096), la = so + r * 128 + ((lane ^ r) & 7) * 16;
        const uint32_t sa = so + (lane >> 4) * 1024 + (lane & 7) * 128 + (((2 * warp4 + ((lane >> 3) & 1)) ^ (lane & 7)) << 4);
        uint4* op = reinterpret_cast<uint4*>(out) + n0 * 8 + (lane & 7);
        float d[32];
        wg_fence();
        rs64z(d, af[8], dsc(dd, DH32B));
#pragma unroll
        for (int ks = 0; ks < 8; ks++) rs64(d, af[ks], dsc(db + (ks >> 2) * (24576 >> 4) + (ks & 3) * 2, DH128));
        wg_commit();
        wg_wait<0>();
        fence_regs<32>(d);
#pragma unroll
        for (int ks = 0; ks < 9; ks++) fence_regs<4>(af[ks]);
#pragma unroll
        for (int j = 0; j < 4; j++) {
            const float* e = d + 8 * j;
            const uint32_t t0 = pack2(e[0], e[1]), t2 = pack2(e[4], e[5]);
            m = amax2(m, amax2(t0, t2));
            stsm4t(sa + j * 2048, bmul2(t0, sc), bmul2(pack2(e[2], e[3]), sc), bmul2(t2, sc), bmul2(pack2(e[6], e[7]), sc));
        }
        asm volatile("bar.sync %0, 128;" ::"r"(11 + blk) : "memory");
#pragma unroll
        for (int j = 0; j < 4; j++) {
            const uint4 v = lds128(la + j * 2048);
            if (n0 + 16 * j != mid && n0 + 16 * j < nrow) op[j * 128] = v;
        }
    }
    __syncwarp();
    return bar_or<7, NT>(((m & 0x7FFF7FFFu) + 0x00800080u) & 0x80008000u);
}

__device__ __forceinline__ void slow_path(uint32_t sb, int bucket, const Args& a) {
    const int tid = threadIdx.x, lane = tid & 31, j = tid & 127, wg = tid >> 7;
    bar_sync<0, NT>();
    for (int i = tid; i < NPB * 128; i += NT) sts32(sb + SM_SAGG + i * 4, 0u);
    if (tid < 192) sts32(sb + SM_DEG + tid * 4, 0u);
    const unsigned short* w1u = reinterpret_cast<const unsigned short*>(a.w1);
    {
        uint32_t w[32];
#pragma unroll
        for (int k = 0; k < 32; k++) w[k] = w1u[(64 + 2 * k) * 128 + j] | ((uint32_t)w1u[(65 + 2 * k) * 128 + j] << 16);
        const float bj = __bfloat162float(a.b1[j]);
        for (int node = wg; node < NPB && bucket * NPB + node < NN; node += 5) {
            const uint4* xr = reinterpret_cast<const uint4*>(a.x + (size_t)(bucket * NPB + node) * 64);
            float h = bj;
            fence_regs<32>(w);
#pragma unroll
            for (int k = 0; k < 8; k++) {
                const uint4 v = __ldg(xr + k);
                const uint32_t vv[4] = {v.x, v.y, v.z, v.w};
#pragma unroll
                for (int i = 0; i < 4; i++) {
                    h = fmaf(bf_lo(vv[i]), bf_lo(w[4 * k + i]), h);
                    h = fmaf(bf_hi(vv[i]), bf_hi(w[4 * k + i]), h);
                }
            }
            sts32(sb + SM_SQ + (node * 128 + j) * 4, __float_as_uint(h));
        }
    }
    for (int k = wg; k < 40; k += 5) {
        const int r = k < 32 ? 2 * k : 2 * k + 64;
        sts32(sb + SM_SW + (k * 128 + j) * 4, w1u[r * 128 + j] | ((uint32_t)w1u[(r + 1) * 128 + j] << 16));
    }
    bar_sync<0, NT>();
    for (int e0 = wg * 32; e0 < NE; e0 += 160) {
        const int dn = a.dst[e0 + lane] - bucket * NPB;
        unsigned m = __ballot_sync(0xFFFFFFFFu, dn >= 0 && dn < NPB);
        while (m) {
            const int l = __ffs(m) - 1;
            m &= m - 1;
            const int node = __shfl_sync(0xFFFFFFFFu, dn, l);
            const int e = e0 + l;
            const uint4* xr = reinterpret_cast<const uint4*>(a.x + (size_t)a.src[e] * 64);
            const uint4* er = reinterpret_cast<const uint4*>(a.ea + (size_t)e * 16);
            float h = __uint_as_float(lds32(sb + SM_SQ + (node * 128 + j) * 4));
#pragma unroll
            for (int k = 0; k < 10; k++) {
                const uint4 v = (k < 8) ? __ldg(xr + k) : __ldg(er + (k - 8));
                const uint32_t vv[4] = {v.x, v.y, v.z, v.w};
#pragma unroll
                for (int i = 0; i < 4; i++) {
                    const uint32_t w = lds32(sb + SM_SW + ((4 * k + i) * 128 + j) * 4);
                    h = fmaf(bf_lo(vv[i]), bf_lo(w), h);
                    h = fmaf(bf_hi(vv[i]), bf_hi(w), h);
                }
            }
            h *= 0.5f;
            const float f = fmaf(h, tanh_fast(h), h);
            asm volatile("red.shared.add.f32 [%0], %1;" ::"r"(sb + SM_SAGG + (node * 128 + j) * 4), "f"(f) : "memory");
            if (j == 0) atoms_add<1>(sb + SM_DEG + node * 4);
        }
    }
    bar_sync<0, NT>();
    load_w2(sb, tid, NT, a);
    for (int i = tid; i < NPB * 64; i += NT) {
        const int node = i >> 6, pr = i & 63;
        const float u = __uint_as_float(lds32(sb + SM_SAGG + (node * 128 + 2 * pr) * 4));
        const float v = __uint_as_float(lds32(sb + SM_SAGG + (node * 128 + 2 * pr + 1) * 4));
        const int ch = (pr & 31) >> 2;
        sts32(sb + SM_QA + (pr >> 5) * 24576 + node * 128 + ((ch ^ (node & 7)) << 4) + (pr & 3) * 4, pack2(u, v));
    }
    fence_async();
    bar_sync<0, NT>();
    if (wg >= 3) return;
    const int wu = __shfl_sync(0xFFFFFFFFu, wg, 0);
    const int q = lane & 3, node0 = wg * 64 + ((tid >> 5) & 3) * 16 + (lane >> 2);
    float d[32];
#pragma unroll
    for (int i = 0; i < 32; i++) d[i] = 0.f;
    wg_fence();
#pragma unroll
    for (int ks = 0; ks < 8; ks++)
        ss64t(d, mkdesc(sb + SM_QA + (ks >> 2) * 24576 + wu * 8192 + (ks & 3) * 32, 16, 1024, 1), mkdesc(sb + SM_W2 + ks * 2048, 16, 1024, 1), ks);
    wg_commit();
    wg_wait<0>();
    fence_regs<32>(d);
    const uint4 bb0 = lds128(sb + SM_B2 + q * 32), bb1 = lds128(sb + SM_B2 + q * 32 + 16);
    const uint32_t bw[8] = {bb0.x, bb0.y, bb0.z, bb0.w, bb1.x, bb1.y, bb1.z, bb1.w};
#pragma unroll
    for (int r = 0; r < 2; r++) {
        const int node = node0 + 8 * r, gn = bucket * NPB + node;
        const uint32_t dg = lds32(sb + SM_DEG + node * 4);
        const float fd = (float)dg;
        uint32_t o[8];
#pragma unroll
        for (int i = 0; i < 8; i++) o[i] = dg ? pack2(fmaf(fd, bf_lo(bw[i]), d[4 * i + 2 * r]), fmaf(fd, bf_hi(bw[i]), d[4 * i + 2 * r + 1])) : 0u;
        if (node < NPB && gn < NN) {
            uint4* op = reinterpret_cast<uint4*>(a.out + (size_t)gn * 64 + 16 * q);
            op[0] = make_uint4(o[0], o[1], o[2], o[3]);
            op[1] = make_uint4(o[4], o[5], o[6], o[7]);
        }
    }
}

template <int MODE>
__device__ __forceinline__ bool producer(uint32_t sb, const Args& a) {
    const int tid = threadIdx.x, lane = tid & 31, warp = tid >> 5, warp4 = warp & 3, u = tid - 512;
    const int cta = blockIdx.x;
    const int nrow = min(NPB, NN - cta * NPB);
    asm volatile("setmaxnreg.dec.sync.aligned.u32 64;");
    const uint32_t ts = clock();
    const uint32_t ep = MODE == 3 ? ld_g32(a.ctl + 32 + 32 * cta) + 1 : 0;
    auto wait_rows = [&]() {
        int it = 0;
        while ((int)(ld_acq32(a.ctl) - ep * G) < 0)
            if (++it > (1 << 22)) __trap();
        CSTAMP(13, warp4 == 3);
    };
    auto load_w1 = [&](int j0, int j1) {
        const int r = u >> 4, c = u & 15;
        const uint32_t sw = r * 128 + (((c & 7) ^ r) << 4);
        const __nv_bfloat16* wp = a.w1 + u * 8;
#pragma unroll
        for (int j = j0; j < j1; j++) {
            const uint32_t d = j < 8 ? SM_W1A + j * 1024 : j < 16 ? SM_W1B + (j - 8) * 1024 : SM_W1A + (j - 8) * 1024;
            cp16(sb + d + (c >> 3) * (j < 8 || j >= 16 ? 10240 : 8192) + sw, wp + j * 1024);
        }
    };
    if (MODE & 2) {
        if (u == 32) {
#pragma unroll
            for (int i = 0; i < 4; i++) {
                mbar_init(sb + SM_BAR + i * 8, 128 + 4);
                mbar_init(sb + SM_BAR + 32 + i * 8, 8);
            }
            mbar_init(sb + B_X, 128);
            mbar_init(sb + B_W, 256);
            mbar_init(sb + B_V, 128);
            mbar_init(sb + B_T, 96);
        }
        if (u == 64 && cta == G - 1 && MODE == 3) { l2_prefetch(a.w2, 16384); l2_prefetch(a.b2, 128); }
        __syncwarp();
    }
    if (MODE & 2) {
        load_w1(0, 18);
        if (u < 16) cp16(sb + SM_B1 + u * 16, a.b1 + u * 8);
        bar_sync<10, 128>();
        mbar_cp_arrive(sb + B_V);
    }
    bar_sync<9, 160>();
    {
        const int xrow = u >> 3;
        const uint32_t xa = sb + SM_XO + xrow * 128 + (((u & 7) ^ (xrow & 7)) << 4);
        const __nv_bfloat16* xp = a.x + (size_t)cta * NPB * 64 + (u & 7) * 8;
#pragma unroll
        for (int j = 0; j < 12; j++) cp16z(xa + j * 2048, xp + min(xrow + 16 * j, nrow - 1) * 64, xrow + 16 * j >= nrow);
        cp_commit();
        if ((MODE & 2) && !BXF) mbar_cp_arrive(sb + B_X);
        cp_commit();
        if (BXF && (MODE & 2)) {
            cp_wait<0>();
            fence_async();
            mbar_arrive(sb + B_X);
        }
        cp_wait<1>();
        CSTAMP(20, u == 0);
        if ((MODE & 2) && u == 0 && (SRCP == 0 || MODE != 3)) l2_prefetch(a.src + cta * CH, min(CH, NE - cta * CH) * 4);
        __syncwarp();
        const uint32_t r1 = 96 + min(u, G - 97), c0 = cta - u + (u > cta ? G : 0), c1 = cta - r1 + (r1 > cta ? G : 0);
        const uint32_t* lp = a.ctl + C_LEN + cta;
        uint32_t n0 = 0, n1 = 0;
        if ((MODE & 2) && LENP == 2 && warp4 != 3) { n0 = ld_rlx32(lp + c0 * 160); n1 = ld_rlx32(lp + c1 * 160); }
        auto check_w1 = [&]() {
            mbar_wait(sb + B_V, 0);
            if (u < 80) {
                uint32_t m = 0;
#pragma unroll
                for (int c = 0; c < 16; c++) {
                    const uint4 v = lds128(sb + SM_W1A + (c >> 3) * 10240 + u * 128 + (((c & 7) ^ (u & 7)) << 4));
                    m = amax2(m, amax2(amax2(v.x, v.y), amax2(v.z, v.w)));
                }
                m = amax_fin(m);
                if (m != 0 && m < 0x3A00u) sts32(sb + F_BAD, 1u);
                asm volatile("red.shared.max.u32 [%0], %1;" ::"r"(sb + F_WMAX), "r"(m) : "memory");
            }
            __syncwarp();
        };
        auto conv_x = [&]() {
#pragma unroll
            for (int j0 = 0; j0 < 12; j0 += 6) {
                uint4 v[6];
#pragma unroll
                for (int j = 0; j < 6; j++) v[j] = lds128(xa + (j0 + j) * 2048);
#pragma unroll
                for (int j = 0; j < 6; j++) sts128(sb + SM_XR + u * 16 + (j0 + j) * 2048, bf2h(v[j].x), bf2h(v[j].y), bf2h(v[j].z), bf2h(v[j].w));
            }
            CSTAMP(36, u == 0);
            fence_async();
            if (warp4 != 3) bar_arrive<4, MODE == 3 ? 160 : 128>();
        };
        if ((MODE & 1) && (XRP == 0 || MODE != 3 || warp4 == 3)) conv_x();
        if ((MODE & 2) && warp4 != 3) {
            CSTAMP(34, u == 0);
            if (LENP == 0) { n0 = ld_rlx32(lp + c0 * 160); n1 = ld_rlx32(lp + c1 * 160); }
            if (W1P == 0) check_w1();
            if (warp4 == 2) {
                const uint32_t r = 128 + (lane >> 3), c = cta - r + (r > cta ? G : 0);
                sts32(sb + SM_UT + lane * 4, c * ((1u << 24) + G * RU) + r * RU + (lane & 7));
            }
            CSTAMP(38, u == 0);
            if (LENP == 1) { n0 = ld_rlx32(lp + c0 * 160); n1 = ld_rlx32(lp + c1 * 160); }
            int it = 0;
            while (MODE == 3 && ((n0 ^ (ep << 13)) | (n1 ^ (ep << 13))) >> 13) {
                if (++it > (1 << 22)) __trap();
                n0 = ld_rlx32(lp + c0 * 160);
                n1 = ld_rlx32(lp + c1 * 160);
            }
            __syncwarp();
            CSTAMP(35, u == 0);
            n0 &= 0x1FFFu;
            n1 = u < G - 96 ? n1 & 0x1FFFu : 0u;
            const uint32_t k0 = max((min(n0, RS) + 3) >> 2, 8u) - 8, k1 = max((min(n1, RS) + 3) >> 2, 8u) - 8;
            uint32_t t0;
            asm volatile("atom.shared.add.u32 %0, [%1], %2;" : "=r"(t0) : "r"(sb + F_UN), "r"(k0 + k1) : "memory");
            t0 = sb + SM_UT + t0 * 4;
            const uint32_t t1 = t0 + k0 * 4;
            const uint32_t e0 = c0 * ((1u << 24) + G * RU) + u * RU + 8, e1 = c1 * ((1u << 24) + G * RU) + r1 * RU + 8;
            CSTAMP(30, u == 0 && t0 != 1);
#pragma unroll
            for (uint32_t j = 0; j < RU - 8; j++)
                if (j < k0) sts32(t0 + j * 4, e0 + j);
            if (warp4 < 2) {
#pragma unroll
                for (uint32_t j = 0; j < RU - 8; j++)
                    if (j < k1) sts32(t1 + j * 4, e1 + j);
            }
            mbar_arrive(sb + B_T);
            CSTAMP(37, u == 0);
            if (XRP == 1 && MODE == 3) conv_x();
            if (W1P == 1) check_w1();
            __syncwarp();
            recv_extra<MODE>(sb, n0, c0, ep, a);
            recv_extra<MODE>(sb, n1, c1, ep, a);
            mbar_wait(sb + B_T, 0);
            const uint32_t un = lds32(sb + F_UN), tg = (((MODE == 3 ? ep : 1u) & 255u) + 256u) << 13, pw = tg + 0xC0000000u + (lane << 24);
#pragma unroll 1
            for (uint32_t i = PTL + u; i - lane < un; i += 96) {
                const uint32_t e = lds32(sb + SM_UT + i * 4);
                uint4 rv = make_uint4(pw, pw, pw, pw);
                ld_rec_if(rv, i < un, a.ra + (e & 0xFFFFFFu));
                if (MODE == 3) await(rv, tg, a.ra + (e & 0xFFFFFFu));
                drop(sb, rv, (e >> 24) * CH - tg, CINC);
                __syncwarp();
            }
        }
        if (MODE & 2) bar_arrive<3, NT>();
        if ((MODE & 1) && warp4 < 2 && cta == G - 1) convert_w2(sb, u, ep, a);
        if ((MODE & 1) && warp4 == 3) {
            bar_sync<4, MODE == 3 ? 160 : 128>();
            if (lane == 0) {
                const int nr = min(NPB, NN + 1 - cta * NPB);
                if (MODE == 3 && SRCP == 1) l2_prefetch(a.src + cta * CH, min(CH, NE - cta * CH) * 4);
                uint32_t t0 = clock();
                const uint32_t dt = PDL ? max((int)(ts + PDL - t0), 0) * (PROWS * 1024 / 192) >> 10 : PDT;
#pragma unroll 1
                for (int r = 0; r < nr; r += PROWS) {
                    bulk_store(a.xh + ((size_t)cta * NPB + r) * 8, sb + SM_XR + r * 128, min(PROWS, nr - r) * 128);
                    if (MODE == 3 && SRCP >= 3 && r >= SRS) {
                        const int o = (r - SRS) * (6144 / (192 - SRS)), n = min(min(CH, NE - cta * CH) - o, PROWS * (6144 / (192 - SRS)));
                        if (n > 0) l2_prefetch(a.src + cta * CH + o, n * 4);
                    }
                    while (MODE == 3 && (int)(clock() - t0) < (int)dt) {}
                    t0 += dt;
                }
                if (MODE == 3 && (SRCP == 2 || (SRCP == 3 && cta == G - 1))) l2_prefetch(a.src + cta * CH, min(CH, NE - cta * CH) * 4);
                bulk_wait();
                CSTAMP(14, true);
                if (MODE == 3) {
                    asm volatile("red.release.gpu.global.add.u32 [%0], 1;" ::"l"(a.ctl) : "memory");
                    a.ctl[32 + 32 * cta] = ep;
                    CSTAMP(16, true);
                    if (!LATEW) wait_rows();
                }
            }
            __syncwarp();
        }
    }
    if (!(MODE & 2)) return false;
    const char* xb = reinterpret_cast<const char*>(a.xh) + (lane & 7) * 16;
    const char* eb = reinterpret_cast<const char*>(a.ea) + (lane & 1) * 16;
    const char* sp = reinterpret_cast<const char*>(a.src);
    const int oc = warp4 * 32 + lane;
    const uint32_t posa = sb + SM_POS + col2pos(oc) * 2;
    auto lookup = [&](int t) { return lds32(sb + SM_BIN + lds16(posa + t * 256)); };
    const uint32_t raw = sb + SM_RAW + u * 16, sring = sb + SM_SR + oc * 4;
    auto fetch_s = [&](int slot, uint32_t rec) {
        if (rec & PADW) sts32(sring + slot * 512, NN);
        else cp4(sring + slot * 512, madw(rec & 0xFFFFFu, 4u, sp));
    };
    auto fetch_e = [&](int slot, uint32_t rec) {
        const uint32_t l0 = __shfl_sync(0xFFFFFFFFu, rec, lane >> 1), l1 = __shfl_sync(0xFFFFFFFFu, rec, 16 + (lane >> 1));
        cp16z(raw + slot * 4096, madw(l0 & 0xFFFFFu, 32u, eb), l0 & PADW);
        cp16z(raw + slot * 4096 + 2048, madw(l1 & 0xFFFFFu, 32u, eb), l1 & PADW);
    };
    auto fetch = [&](int slot, uint32_t rec) { fetch_s(slot, rec); fetch_e(slot, rec); };
    const int xc0 = warp4 * 32 + (lane >> 4) * 16 + ((lane >> 3) & 1) * 4;
    const uint32_t slist = sb + SM_SR + xc0 * 4;
    uint32_t xoff[4];
#pragma unroll
    for (int i = 0; i < 4; i++) xoff[i] = sb + SM_XE + (xc0 + i) * 128 + (((lane & 7) ^ ((xc0 + i) & 7)) << 4);
    const int ec = warp4 * 32 + (lane >> 1);
    const uint32_t eoff = sb + SM_XE + 16384 + ec * 32 + (((lane & 1) ^ ((ec >> 2) & 1)) << 4);
    const uint32_t ioff = sb + SM_IND + oc * 32 + (((oc >> 2) & 1) << 4);
    auto put_x = [&](const uint4& la, const uint4& lb, uint32_t so) {
        const uint32_t lw[8] = {la.x, la.y, la.z, la.w, lb.x, lb.y, lb.z, lb.w};
#pragma unroll
        for (int i = 0; i < 4; i++) {
            cp16(xoff[i] + so, madw(lw[i], 128u, xb));
            cp16(xoff[i] + so + 1024, madw(lw[4 + i], 128u, xb));
        }
        cp_commit();
    };
    auto put_e = [&](const uint32_t* ef, uint32_t cur, uint32_t so, uint32_t ia) {
        sts128(eoff + so, ef[0], ef[1], ef[2], ef[3]);
        sts128(eoff + so + 512, ef[4], ef[5], ef[6], ef[7]);
        sts128(ia, 0u, 0u, 0u, 0u);
        sts128(ia ^ 16, 0u, 0u, 0u, 0u);
        if (!(cur & PADW)) sts16(ia ^ ((cur >> 23) & 30u), 0x3C00u);
    };
    auto publish = [&](uint32_t bar, uint32_t cnt) {
        fence_async();
        __syncwarp();
        if (lane == 0) asm volatile("mbarrier.arrive.shared::cta.b64 _, [%0], %1;" ::"r"(bar), "r"(cnt) : "memory");
    };
    asm volatile("" : "+l"(xb), "+l"(eb), "+l"(sp));
    __syncwarp();
    bar_sync<5, NT>();
    const uint4 fl = lds128(sb + F_TOT);
    const uint32_t p0 = lds16(posa), p1 = lds16(posa + 256);
    const int T = fl.z ? 0 : ((int)fl.x + 63) >> 6;
    CSTAMP(17, u == 0 && T >= 0);
    const int T0 = (T + 1) >> 1, T1 = T >> 1;
    uint32_t own[4] = {PADW, PADW, PADW, PADW};
    auto first_x = [&](int s) {
        __syncwarp();
        const uint4 la = lds128(slist + s * 512), lb = lds128(slist + s * 512 + 32);
        const uint32_t lw[8] = {la.x, la.y, la.z, la.w, lb.x, lb.y, lb.z, lb.w};
#pragma unroll
        for (int i = 0; i < 8; i++)
            cp16z(xoff[i & 3] + s * XE_S + (i >> 2) * 1024, madw(lw[i], 128u, xb), lw[i] == NN);
        cp_commit();
        mbar_cp_arrive(sb + SM_BAR + s * 16);
    };
    auto first_e = [&](int s) {
        const uint4 e0 = lds128(raw + s * 4096), e1 = lds128(raw + s * 4096 + 2048);
        const uint32_t ef[8] = {bf2h(e0.x), bf2h(e0.y), bf2h(e0.z), bf2h(e0.w), bf2h(e1.x), bf2h(e1.y), bf2h(e1.z), bf2h(e1.w)};
        put_e(ef, own[s], s * XE_S, ioff + s * 4096);
        __syncwarp();
        if (lane == 0) mbar_arrive(sb + SM_BAR + s * 16);
    };
    if (T > 0) own[0] = lds32(sb + SM_BIN + p0);
    if (T > 1) own[1] = lookup(T - 1);
    fetch_s(0, own[0]);
    fetch_s(1, own[1]);
    cp_commit();
    if (MODE == 3 && LATEW == 5) {
        if (u == 96) wait_rows();
        __syncwarp();
    }
    fetch_e(0, own[0]);
    cp_commit();
    if (MODE == 3 && LATEW == 6) {
        if (u == 96) wait_rows();
        __syncwarp();
    }
    CSTAMP(18, u == 0);
    if (T > 2) own[2] = lds32(sb + SM_BIN + p1);
    if (T > 3) own[3] = lookup(T - 2);
    uint32_t r2 = PADW, pc = lds16(posa + max(T - 3, 0) * 256);
    if (T > 4) r2 = lookup(2);
    if (MODE == 3 && LATEW && LATEW < 3) {
        if (lane == 0 && (LATEW == 2 || warp4 == 3)) wait_rows();
        __syncwarp();
        if (LATEW == 1) bar_sync<15, 128>();
    }
    cp_wait<1>();
    CSTAMP(21, u == 0);
    if (MODE == 3 && LATEW == 3) bar_sync<15, 160>();
    if (MODE == 3 && LATEW >= 5) bar_sync<15, 128>();
    if (MODE == 3 && LATEW == 4) {
        uint32_t f;
        int it = 0;
        do {
            asm volatile("ld.acquire.cta.shared.u32 %0, [%1];" : "=r"(f) : "r"(sb + F_ROWS) : "memory");
            if (++it > (1 << 24)) __trap();
        } while (f == 0);
    }
    first_x(0);
    fetch_e(1, own[1]);
    cp_commit();
    first_x(1);
    CSTAMP(5, u == 0);
    cp_wait<3>();
    first_e(0);
    fetch(2, own[2]);
    cp_commit();
    cp_wait<2>();
    first_e(1);
    CSTAMP(44, u == 0);
    bar_sync<6, NT>();
    if (lds32(sb + F_BAD)) {
        cp_wait_all();
        asm volatile("setmaxnreg.inc.sync.aligned.u32 96;");
        return true;
    }
    CSTAMP(45, u == 0);
    fetch(3, own[3]);
    cp_commit();
    cp_commit();
    CSTAMP(26, u == 0);
    int i3 = 8192;
    uint32_t pb = 0, r0 = own[2], r1 = own[3];
    for (int k = 1; k < T0; k++) {
#pragma unroll
        for (int s = 0; s < 2; s++) {
            if (s == 1 && k >= T1) break;
            const int st = 2 * s + (k & 1), slot = 2 * (k & 1) + s;
            cp_wait<2>();
            __syncwarp();
            const uint4 e0 = lds128(raw + slot * 4096), e1 = lds128(raw + slot * 4096 + 2048);
            const uint4 la = lds128(slist + slot * 512), lb = lds128(slist + slot * 512 + 32);
            const uint32_t l0 = __shfl_sync(0xFFFFFFFFu, r2, lane >> 1), l1 = __shfl_sync(0xFFFFFFFFu, r2, 16 + (lane >> 1));
            const uint32_t r3 = lds32(sb + SM_BIN + pc);
            pc = lds16(posa + (s ? max(T - 3 - k, T0) : min(k + 2, T0 - 1)) * 256);
            const uint32_t ef[8] = {bf2h(e0.x), bf2h(e0.y), bf2h(e0.z), bf2h(e0.w), bf2h(e1.x), bf2h(e1.y), bf2h(e1.z), bf2h(e1.w)};
            const uint32_t ia = ioff + i3 + s * 4096;
            const uint32_t so = s * XE_S + (k & 1) * XE_P;
            if (pb) {
                cp_wait<1>();
                publish(pb, 33);
            }
            mbar_wait(sb + SM_BAR + 32 + st * 8, ((k >> 1) & 1) ^ 1);
            CSTAMPV(26 + 2 * k + s, u == 0 && k <= 8);
            pb = sb + SM_BAR + st * 8;
            put_x(la, lb, so);
            if (k < KF) mbar_cp_arrive(pb);
            put_e(ef, r0, so, ia);
            if (k < KF) {
                __syncwarp();
                if (lane == 0) mbar_arrive(pb);
                pb = 0;
            }
            if (k + 1 < (s ? T1 : T0)) {
                fetch_s(slot ^ 2, r2);
                cp16z(raw + (slot ^ 2) * 4096, madw(l0 & 0xFFFFFu, 32u, eb), l0 & PADW);
                cp16z(raw + (slot ^ 2) * 4096 + 2048, madw(l1 & 0xFFFFFu, 32u, eb), l1 & PADW);
            }
            cp_commit();
            r0 = r1;
            r1 = r2;
            r2 = r3;
        }
        i3 = (i3 == 16384) ? 0 : i3 + 8192;
    }
    cp_wait_all();
    if (pb) publish(pb, 33);
    bar_sync<10, 128>();
    prepare_tail<MODE>(sb, u, ep, a);
    const bool small = sums_small(sb, u, T0);
    mbar_wait(sb + B_W, 0);
    if (!bar_or<7, NT>(small || lds32(sb + SM_W2 + 129 * 128 + 4))) return false;
    asm volatile("setmaxnreg.inc.sync.aligned.u32 96;");
    return true;
}

template <int MODE>
__device__ __forceinline__ bool consumer(uint32_t sb, const Args& a) {
    const int tid = threadIdx.x, lane = tid & 31, warp = tid >> 5, wg = tid >> 7, warp4 = warp & 3;
    const int cta = blockIdx.x;
    uint32_t ep = 1;
    uint4 dv[3];
    const int nv = min(CH, NE - cta * CH) >> 2;
    uint32_t pm = 0;
    auto prefetch_e = [&]() {
        if (MODE != 3 || !PFA) return;
        const char* pe = reinterpret_cast<const char*>(a.ea) + ((size_t)cta * CH + tid * 4) * 32;
#pragma unroll
        for (int i = 0; i < 12; i++)
            asm volatile("{.reg .pred q; setp.ne.u32 q, %0, 0; @q prefetch.global.L2 [%1];}" ::"r"(pm & (1u << i)), "l"(pe + (i >> 2) * 65536 + 32 * (i & 3)) : "memory");
    };
    {
        if (MODE == 3) ep = ld_g32(a.ctl + 32 + 32 * cta);
        if (MODE & 1) {
            const int* dp = a.dst + cta * CH + tid * 4;
            dv[0] = ld_stream(dp);
            dv[1] = ld_stream(dp + 2048);
            dv[2] = ld_stream(tid + 1024 < nv ? dp + 4096 : dp);
        }
        if (tid >= 8 && tid < 16) sts32(sb + SM_FLAG + (tid - 8) * 4, 0u);
        if (tid == 16) sts32(sb + SM_BIN + PADO, PADW);
        if (tid == 17) sts32(sb + F_MID, NPB);
        if (tid == 18) sts32(sb + F_UN, 32u);
        if (tid == 19) sts32(sb + F_ROWS, 0u);
        if (tid >= 448) sts128(sb + SM_TT + (tid - 448) * 16, 0u, 0u, 0u, 0u);
        __syncwarp();
        if (tid >= 64 && tid < 288)
            sts32(sb + SM_DEG + (tid - 64) * 4, tid >= 256 ? 0xC0000000u : (1u << 18) + sb + SM_BIN + (tid - 64 < NPB ? (tid - 64) * BINP : PADO));
        else if (tid >= 288 && tid < 288 + G) {
            sts32(sb + SM_CNT + (tid - 288) * 4, sb + SM_STA + (tid - 288 + (tid - 288 < cta ? G : 0) - cta) * RP);
            sts32(sb + SM_XC + (tid - 288) * 4, 0u);
        }
        if (MODE == 3) ep++;
        const uint32_t tg = ((ep & 255u) + 256u) << 13;
        if (MODE & 1) {
            const uint32_t pw = tg + 0xC0000000u + (lane << 24);
#pragma unroll
            for (int j = 0; j < 5; j++)
                if (tid + 512 * j < G * RU) sts128(sb + SM_STA + tid * 16 + j * 8192, pw, pw, pw, pw);
        }
        CSTAMP(22, tid == 0);
        bar_sync<2, 512>();
        if (MODE == 2) {
            if (warp == 0) bar_sync<9, 160>();
            bar_sync<2, 512>();
        }
        if (MODE & 1) {
            uint32_t mask = 0, inc = CINC;
            asm volatile("" : "+r"(inc));
#pragma unroll
            for (int j = 0; j < 3; j++)
                if (j < 2 || tid + 1024 < nv) {
                    const uint32_t dd[4] = {dv[j].x, dv[j].y, dv[j].z, dv[j].w};
                    uint32_t w[4], pa[4];
#pragma unroll
                    for (int k = 0; k < 4; k++) {
                        const uint32_t b = __umulhi(dd[k], 22605092u);
                        pa[k] = atoms_addr(sb + SM_CNT + b * 4, inc);
                        w[k] = (dd[k] << 24) + (tg + tid * 4 + j * 2048 + k) - b * ((uint32_t)NPB << 24);
                    }
                    if (j == XAT && warp == 0) bar_sync<9, 160>();
                    if (j == 0) CSTAMP(2, tid == 0);
                    put<RUNL, 1u>(pa[0], w[0], mask);
                    put<RUNL, 2u>(pa[1], w[1], mask);
                    put<RUNL, 4u>(pa[2], w[2], mask);
                    put<RUNL, 8u>(pa[3], w[3], mask);
                    mask <<= 4;
                }
            CSTAMP(3, tid == 0);
            fence_async();
            __syncwarp();
            bar_sync<2, 512>();
            if (warp == 0) {
                uint32_t n[5];
#pragma unroll
                for (int j = 0; j < 5; j++) n[j] = lds32(sb + SM_CNT + (lane + 32 * j) * 4);
#pragma unroll
                for (int j = 0; j < 5; j++)
                    if (lane + 32 * j < G) st_rlx32(a.ctl + C_LEN + cta * 160 + lane + 32 * j, (ep << 13) + (n[j] >> 18));
                __syncwarp();
            }
            if (tid == 0) {
                bulk_store(a.ra + (size_t)cta * (G * RU), sb + SM_STA, G * RP);
                if (MODE == 1) bulk_wait();
            }
            CSTAMP(40, tid == 0);
            __syncwarp();
            if (__builtin_expect(mask != 0, 0)) send_extra(sb, tid + 1024 < nv ? mask : mask << 4, ep, a);
            __syncwarp();
        }
    }
    if (!(MODE & 2)) return false;
    asm volatile("setmaxnreg.inc.sync.aligned.u32 104;");
    CSTAMP(4, tid == 0);
    const int s = wg >> 1, h = wg & 1;
    uint32_t w1f[5][4];
    auto load_w1f = [&]() {
        const int kr = (lane & 7) + 8 * (lane >> 4), ch = 2 * warp4 + ((lane >> 3) & 1);
#pragma unroll
        for (int ks = 0; ks < 5; ks++) {
            ldsm4t(w1f[ks], sb + SM_W1A + h * 10240 + (16 * ks + kr) * 128 + ((ch ^ (kr & 7)) << 4));
#pragma unroll
            for (int i = 0; i < 4; i++) w1f[ks][i] = pack2h(0.5f * bf_lo(w1f[ks][i]), 0.5f * bf_hi(w1f[ks][i]));
        }
#pragma unroll
        for (int ks = 0; ks < 5; ks++) pin(ep, sb + SM_PIN, w1f[ks][0], w1f[ks][1], w1f[ks][2], w1f[ks][3]);
    };
    mbar_wait(sb + B_V, 0);
    if (!WA) load_w1f();
    if (MODE == 3 && PFA) {
#pragma unroll
        for (int j = 0; j < 3; j++) {
            const uint32_t dd[4] = {dv[j].x, dv[j].y, dv[j].z, dv[j].w};
#pragma unroll
            for (int k = 0; k < 4; k++)
                if (dd[k] - PFA - __umulhi(dd[k], 22605092u) * NPB >= NPB - PFA - PFB) pm |= 1u << (4 * j + k);
        }
        if (tid + 1024 >= nv) pm &= 255u;
        asm volatile("" : "+r"(pm));
    }
    if (MODE == 3 && PFA) pin(ep, sb + SM_PIN, pm, pm, pm, pm);
    CSTAMP(41, tid == 0);
    if (PFL == 0) prefetch_e();
    auto head = [&](uint32_t r) { return (cta - r + (r > cta ? G : 0)) * ((1u << 24) + G * RU) + r * RU + (tid & 7); };
    uint32_t en;
    uint4 nx;
    auto gate = [&]() {
        en = head(tid >> 3);
        CSTAMP(47, tid == 0);
        if (MODE == 3) {
            if (tid == 0) bulk_wait_read();
            CSTAMP(46, tid == 0);
            __syncwarp();
            bar_sync<2, 512>();
            if (warp == 3) bar_arrive<4, 160>();
            if (GD) { const uint32_t t0 = clock(); while ((uint32_t)clock() - t0 < GD) {} }
        }
        nx = ld_rec(a.ra + (en & 0xFFFFFFu));
    };
    mbar_wait(sb + B_X, 0);
    CSTAMP(39, tid == 0);
    if (!BXF) fence_async();
    {
        float d[48];
        const int wq = WA ? __shfl_sync(0xFFFFFFFFu, wg, 0) : wg;
        q_gemm(d, mkdesc(sb + SM_W1B + (wq & 1) * 8192, 16, 1024, 1), mkdesc(sb + SM_XO + (wq >> 1) * 12288, 16, 1024, 1));
        if (PFL == 3) prefetch_e();
        wg_wait<0>();
        fence_regs<48>(d);
        if (EL == 1) gate();
        const float ba = 0.5f * bf_lo(lds16(sb + SM_B1 + (h * 64 + warp4 * 16 + (lane >> 2)) * 2));
        const float bb = 0.5f * bf_lo(lds16(sb + SM_B1 + (h * 64 + warp4 * 16 + (lane >> 2)) * 2 + 16));
        CSTAMP(42, tid == 0);
        const uint32_t qa = sb + SM_QA + h * 24576 + s * 12288 + (lane >> 4) * 1024 + (lane & 7) * 128 +
                            (((2 * warp4 + ((lane >> 3) & 1)) ^ (lane & 7)) << 4);
#pragma unroll
        for (int j = 0; j < 6; j++) {
            const float* e = d + 8 * j;
            if (EL == 2 && j == 3) gate();
            stsm4t(qa + j * 2048, pack2h(fmaf(e[0], 0.5f, ba), fmaf(e[1], 0.5f, ba)), pack2h(fmaf(e[2], 0.5f, bb), fmaf(e[3], 0.5f, bb)),
                   pack2h(fmaf(e[4], 0.5f, ba), fmaf(e[5], 0.5f, ba)), pack2h(fmaf(e[6], 0.5f, bb), fmaf(e[7], 0.5f, bb)));
        }
    }
    CSTAMP(43, tid == 0);
    if (WA) load_w1f();
    CSTAMP(19, tid == 0);
    if (PFL == 2) prefetch_e();
    if (PFL == 1) prefetch_e();
    {
        const uint32_t tg = ((ep & 255u) + 256u) << 13, pw = tg + 0xC0000000u + (lane << 24);
        uint32_t inc = CINC;
        int i = tid - 1024, un = 0;
        asm volatile("" : "+r"(inc));
        if (EL == 0) gate();
        auto load = [&](uint32_t e) {
            uint4 v = make_uint4(pw, pw, pw, pw);
            ld_rec_if(v, i < un, a.ra + (e & 0xFFFFFFu));
            return v;
        };
#pragma unroll 1
        do {
            uint4 rv = nx;
            const uint32_t e = en, c0 = (e >> 24) * CH - tg;
            i += 512;
            if (i < 0) en = head(64 + (tid >> 3));
            else {
                if (i < 512) {
                    mbar_wait(sb + B_T, 0);
                    un = min(lds32(sb + F_UN), PTL);
                }
                en = lds32(sb + SM_UT + min(i, 2815) * 4);
            }
            if (MODE == 3) await(rv, tg, a.ra + (e & 0xFFFFFFu));
            CSTAMP(23, tid == 0 && i == -512);
            CSTAMP(24, tid == 0 && i == 0);
            CSTAMP(25, tid == 0 && i == 512);
            nx = load(en);
            drop(sb, rv, c0, inc);
            __syncwarp();
            if (PFL >= 5 && (i >> 9) == PFL - 6) prefetch_e();
        } while (i - lane < un);
    }
    if (PFL == 4) prefetch_e();
    CSTAMP(7, tid == 0);
    bar_sync<3, NT>();
    int T;
    {
        uint32_t c[6], tot = 0, bef = 0;
#pragma unroll
        for (int j = 0; j < 6; j++) c[j] = lds32(sb + SM_DEG + lane * 4 + j * 128) >> 19;
        const uint32_t own = lds32(sb + SM_DEG + min(warp * 12 + lane, 191) * 4);
        const uint32_t bad = lds32(sb + F_BAD), no = lds32(sb + F_XC);
        CSTAMP(6, tid == 0 && own != 1);
#pragma unroll
        for (int j = 0; j < 6; j++) {
            tot += c[j];
            if (lane + 32 * j < warp * 12) bef += c[j];
        }
        uint32_t inc = own >> 19;
#pragma unroll
        for (int o = 1; o < 16; o <<= 1) {
            const uint32_t w = __shfl_up_sync(0xFFFFFFFFu, inc, o);
            if (lane >= o) inc += w;
        }
        tot = __reduce_add_sync(0xFFFFFFFFu, tot);
        bef = __reduce_add_sync(0xFFFFFFFFu, bef);
        const uint32_t pk = ((bef + inc - (own >> 19)) << 16) + (own >> 18);
        T = (tot + 63) >> 6;
        if (bad == 0 && tot <= CAP / 2) {
            if (lane < 12 && own < BINL + (1u << 18)) sts32(own & 0x3FFFFu, PADW);
            const int l8 = lane & 7;
            const uint32_t val = ((warp * 12 + (lane >> 3)) * BINP + l8 * 8) * 0x10001u + 0x40000u;
#pragma unroll
            for (int r = 0; r < 3; r++) {
                const uint32_t e = __shfl_sync(0xFFFFFFFFu, pk, 4 * r + (lane >> 3));
                const uint32_t ad = sb + SM_POS + (e >> 16) * 4 + l8 * 4, lim = (e & 0xFFFFu) - 2 * l8;
#pragma unroll
                for (int i = 0; i < 3; i++)
                    if ((int)lim > 16 * i + 1) sts32(ad + 32 * i, val + (uint32_t)(r * 4 * BINP + 64 * i) * 0x10001u);
            }
            if (tid < 64 && tot + tid < T * 64) sts32(sb + SM_POS + (tot + tid) * 4, PADO * 0x10001u);
            if (no) {
                if (lane < 12 && own >= BINL && !(own & (1u << 18))) sts16(sb + SM_POS + (pk >> 16) * 4 + (pk & 0xFFFFu) * 2 - 2, PADO);
#pragma unroll 1
                for (uint32_t i = 0; i < no; i += 32) {
                    const uint2 o = lds64(sb + SM_OVL + min(i + lane, OVC - 1u) * 8);
                    const uint32_t n = (o.x >> 24) - warp * 12, e = __shfl_sync(0xFFFFFFFFu, pk, n);
                    if (i + lane < no && n < 12) sts16(sb + SM_POS + (e >> 16) * 4 + (o.y >> 18) * 2 - 2, OVLO + (i + lane) * 8);
                }
            }
        } else if (tid == 0) sts32(sb + F_BAD, 1u);
        if (tid == 0) sts32(sb + F_TOT, tot);
        __syncwarp();
        CSTAMP(8, tid == 0);
        bar_arrive<5, NT>();
        bar_sync<2, 512>();
        CSTAMP(29, tid == 64);
        if (MODE == 3 && LATEW == 4 && warp >= 16 - NPL && lane == 0) {
            const uint32_t t0 = clock();
            while ((uint32_t)clock() - t0 < (15 - warp) * STG) {}
            int it = 0;
            while ((int)(ld_acq32(a.ctl) - ep * G) < 0)
                if (++it > (1 << 22)) __trap();
            asm volatile("st.release.cta.shared.u32 [%0], %1;" ::"r"(sb + F_ROWS), "r"(1u) : "memory");
            CSTAMP(13, warp == 15);
        }
        if (MODE == 3 && LATEW == 3 && warp == 15) {
            if (lane == 0) {
                int it = 0;
                while ((int)(ld_acq32(a.ctl) - ep * G) < 0)
                    if (++it > (1 << 22)) __trap();
                CSTAMP(13, true);
            }
            __syncwarp();
            bar_arrive<15, 160>();
        }
        if (tid < T && lds32(sb + F_BAD) == 0) {
            const int T0 = (T + 1) >> 1;
            const bool up = tid < T0;
            auto node_at = [&](uint32_t pair) { return lds32(sb + SM_BIN + lds16(sb + SM_POS + min(pair, tot - 1) * 4)) >> 24; };
            const uint32_t first = node_at(tid * 64u), last = node_at(tid * 64u + 63u), nb = node_at(up ? tid * 64u + 64u : tid * 64u - 1u);
            const uint32_t cn = up ? last : first, cm = nb == cn && (!up || tid + 1 < T) ? 1u << (cn & 15u) : 0u;
            const uint32_t rm = ((2u << min(last - first, 15u)) - 1u) << (first & 15u);
            const uint32_t w = min(first, 176u) * 128, ta = sb + SM_TT + (up ? tid : 32 + T - 1 - tid) * 16;
            sts32(ta, w);
            sts32(ta + 36, w);
            sts64(ta + 40, (rm | rm >> 16) & ~cm, cm);
            if (cm && tid == T0 - 1) {
                sts32(sb + F_MID, cn);
                sts32(sb + SM_DEG + NPB * 4, lds32(sb + SM_DEG + cn * 4));
            }
            if (tid == T0 - 5 && first >= 64u) sts32(sb + F_EARLY, 1u);
            if (tid == T0 + 4 && last < 128u) sts32(sb + F_EARLY + 4, 1u);
            if (last - first > 15u) sts32(sb + F_BAD, 1u);
        }
        if (tid >= 96 && tid < 104) sts128(sb + SM_ZR + (tid - 96) * 16, 0u, 0u, 0u, 0u);
        if (warp == 2) {
            const uint32_t m = __reduce_max_sync(0xFFFFFFFFu, max(max(max(c[0], c[1]), max(c[2], c[3])), max(c[4], c[5])));
            if (lane == 0) sts32(sb + F_DMAX, 2 * m);
        }
        __syncwarp();
    }
    bar_arrive<6, NT>();
    bar_sync<2, 512>();
    if (lds32(sb + F_BAD)) {
        asm volatile("setmaxnreg.dec.sync.aligned.u32 96;");
        return true;
    }

    uint32_t af[9][4];
    {
        const int wgu = __shfl_sync(0xFFFFFFFFu, wg, 0);
        const int su = wgu >> 1, hu = wgu & 1;
        const int Ts = __shfl_sync(0xFFFFFFFFu, s ? T >> 1 : (T + 1) >> 1, 0);
        if (Ts > 0) {
            const uint32_t sl = (lane & 7) + 8 * (lane >> 4), ch = ((2 * warp4 + ((lane >> 3) & 1)) ^ (lane & 7)) << 4;
            const uint32_t qb = sb + SM_QA + hu * 24576, sr = (sl + (qb >> 7)) & 15;
            uint32_t c0 = qb + (15 - sr) * 128, lo = sr * 128 + ch, zr = sb + SM_ZR + ch, cr = zr + 128 + wgu * 128, lb = 1u << sl;
            asm volatile("" : "+r"(c0), "+r"(lo), "+r"(zr), "+r"(cr), "+r"(lb));
            auto rowa = [&](uint32_t w) { uint32_t r; asm("lop3.b32 %0, %1, %2, 2047, 0xD8;" : "=r"(r) : "r"(w + c0), "r"(lo)); return r; };
            uint32_t acc[32], pk[16], ah[4] = {0u, 0u, 0u, 0u}, qf[4];
#pragma unroll
            for (int i = 0; i < 16; i++) pk[i] = 0u;
            const uint32_t tta = sb + SM_TT + su * 512;
            ldsm4t(qf, rowa(lds32(tta)));
            const uint32_t ifirst = dlo(sb + SM_IND + su * 4096), ilast = ifirst + 1024;
            uint32_t iprev = ifirst, icur = ifirst;
            const uint32_t x0 = dlo(sb + SM_XE + su * XE_S), bar0 = sb + SM_BAR + 2 * su * 8;
            CSTAMP(27, tid == 64);
            for (int k = 0; k < Ts; k++) {
                const uint32_t dx = x0 + (k & 1) * (XE_P >> 4), bar = bar0 + (k & 1) * 8;
                LSTAMP(2, k);
                mbar_wait(bar, (k >> 1) & 1);
                if (k < KF) fence_async();
                LSTAMP(0, k);
                wg_fence();
#pragma unroll
                for (int kk = 0; kk < 4; kk++) h16t(ah, pk + 4 * kk, dsc(iprev + kk * 64, DH32A));
                h128z(acc, w1f[0], dsc(dx, DH128));
                h128(acc, w1f[1], dsc(dx + 2, DH128));
                h128(acc, w1f[2], dsc(dx + 4, DH128));
                h128(acc, w1f[3], dsc(dx + 6, DH128));
                h128(acc, w1f[4], dsc(dx + 1024, DH32B));
                h128(acc, qf, dsc(icur, DH32B));
                wg_commit();
                const uint4 tt = lds128(tta + (k + 1) * 16);
                const uint32_t qa = rowa(tt.x), ka = (tt.w & lb) ? cr : zr, fa = (tt.z & lb) ? rowa(tt.y) : ka;
                wg_wait<0>();
                fence_regs<32>(acc);
                fence_regs<4>(ah);
                fence_regs<4>(qf);
                fence_regs<16>(pk);
                LSTAMP(1, k);
                if (elect()) mbar_arrive(bar + 32);
                stsm4t(fa, ah[0], ah[1], ah[2], ah[3]);
                ldsm4t(qf, qa);
                ldsm4t(ah, ka);
#pragma unroll
                for (int i = 0; i < 16; i++) {
                    const int i0 = (i >> 1) * 4 + (i & 1);
                    pk[i] = hadd2(silu_h2(acc[i0]), silu_h2(acc[i0 + 2]));
                }
                fence_regs<16>(pk);
                iprev = icur;
                icur = icur == ilast ? ifirst : icur + 512;
            }
            wg_fence();
#pragma unroll
            for (int kk = 0; kk < 4; kk++) h16t(ah, pk + 4 * kk, dsc(iprev + kk * 64, DH32A));
            wg_commit();
            const uint4 tt = lds128(tta + (Ts + 1) * 16);
            const uint32_t sp = qb + (NPB + su) * 128 + (((2 * warp4 + ((lane >> 3) & 1)) ^ ((NPB + su) & 7)) << 4);
            const uint32_t fa = (tt.z & lb) ? rowa(tt.y) : (tt.w & lb) ? sp : zr;
            load_w2t<0, NSH>(sb, warp4, lane, af);
            wg_wait<0>();
            fence_regs<4>(ah);
            fence_regs<16>(pk);
            stsm4t(fa, ah[0], ah[1], ah[2], ah[3]);
        } else load_w2t<0, NSH>(sb, warp4, lane, af);
    }
    CSTAMP(10, tid == 0);
    CSTAMP(31, tid == 128);
    CSTAMP(32, tid == 256);
    CSTAMP(33, tid == 384);
    const bool failed = tail(sb, TWG, __shfl_sync(0xFFFFFFFFu, T, 0), warp4, lane, af, a.out);
    CSTAMP(15, tid == 0);
    if (!failed) return false;
    asm volatile("setmaxnreg.dec.sync.aligned.u32 96;");
    return true;
}

template <int MODE>
__global__ void __launch_bounds__(NT, 1) mpnn_kernel(const __grid_constant__ Args a) {
    extern __shared__ __align__(1024) uint8_t smem[];
    const uint32_t sb = (uint32_t)__cvta_generic_to_shared(smem);
    TSTAMP(0, threadIdx.x == 0);
    CSTAMP(1, threadIdx.x == 0);
    const bool slow = threadIdx.x >= 512 ? producer<MODE>(sb, a) : consumer<MODE>(sb, a);
    if ((MODE & 2) && slow) slow_path(sb, blockIdx.x, a);
    CSTAMP(11, threadIdx.x == 0);
    TSTAMP(12, threadIdx.x == 0);
}

}

extern "C" void kernel_launch(void* const* d_in, const int* in_sizes, int n_in, void* d_out, int out_size) {
    (void)in_sizes; (void)n_in; (void)out_size;
    static int fused = -1;
    static void *p_ra, *p_rx, *p_xh, *p_ctl, *p_w2;
    if (fused < 0) {
        cudaGetSymbolAddress(&p_ra, g_ra);
        cudaGetSymbolAddress(&p_rx, g_rx);
        cudaGetSymbolAddress(&p_xh, g_xh);
        cudaGetSymbolAddress(&p_ctl, g_ctl);
        cudaGetSymbolAddress(&p_w2, g_w2);
        int dev = 0, sms = 0, nb = 0;
        cudaGetDevice(&dev);
        cudaDeviceGetAttribute(&sms, cudaDevAttrMultiProcessorCount, dev);
        cudaFuncSetAttribute(mpnn_kernel<1>, cudaFuncAttributeMaxDynamicSharedMemorySize, SM_TOTAL);
        cudaFuncSetAttribute(mpnn_kernel<2>, cudaFuncAttributeMaxDynamicSharedMemorySize, SM_TOTAL);
        cudaFuncSetAttribute(mpnn_kernel<3>, cudaFuncAttributeMaxDynamicSharedMemorySize, SM_TOTAL);
        cudaOccupancyMaxActiveBlocksPerMultiprocessor(&nb, mpnn_kernel<3>, NT, SM_TOTAL);
        fused = (sms * nb >= G) ? 1 : 0;
    }
    Args a;
    a.x   = (const __nv_bfloat16*)d_in[0];
    a.ea  = (const __nv_bfloat16*)d_in[1];
    a.src = (const int*)d_in[2];
    a.dst = (const int*)d_in[3];
    a.w1  = (const __nv_bfloat16*)d_in[4];
    a.b1  = (const __nv_bfloat16*)d_in[5];
    a.w2  = (const __nv_bfloat16*)d_in[6];
    a.b2  = (const __nv_bfloat16*)d_in[7];
    a.out = (__nv_bfloat16*)d_out;
    a.ra  = (uint4*)p_ra;
    a.rx  = (uint2*)p_rx;
    a.xh  = (uint4*)p_xh;
    a.ctl = (uint32_t*)p_ctl;
    a.w2h = (uint4*)p_w2;
    cudaStream_t s = cudaStreamPerThread;
    if (fused) {
        mpnn_kernel<3><<<G, NT, SM_TOTAL, s>>>(a);
    } else {
        mpnn_kernel<1><<<G, NT, SM_TOTAL, s>>>(a);
        mpnn_kernel<2><<<G, NT, SM_TOTAL, s>>>(a);
    }
}
```
